```python
import torch

def _softmax(x, axis=-1):
    return torch.softmax(x, dim=axis)
def _gelu(x):
    return torch.nn.functional.gelu(x, approximate="tanh")
def _silu(x):
    return torch.nn.functional.silu(x)
def _sigmoid(x):
    return torch.sigmoid(x)
def _layernorm(x, axis=-1, eps=1e-5):
    m = x.mean(dim=axis, keepdim=True)
    v = x.var(dim=axis, keepdim=True, unbiased=False)
    return (x - m) / torch.sqrt(v + eps)
def _scatter_add(tgt, idx, src, axis=0):
    return tgt.clone().index_add_(axis, idx, src)
def _segment_sum(src, seg, n):
    out = torch.zeros((n,) + src.shape[1:], dtype=src.dtype)
    return out.index_add_(0, seg, src)
def _pad(x, pw):
    flat = tuple(v for pair in reversed(pw) for v in pair)
    return torch.nn.functional.pad(x, flat)

kernel_name = 'concat_heads__mha_block_cached__mha_block_cached__near_ridge'

def setup_inputs():

    _w = (lambda a: (lambda t: t.to(torch.bfloat16) if t.is_floating_point() else t)(torch.as_tensor(a)))
    def _A_setup():
        B, Sq, D = 8, 304, 448
        H, Sk, Dh = 16, 1024, 256
        return {
            "x": _w((lambda *s: torch.randn(*s, dtype=torch.bfloat16) * 0.8)(B, Sq, D)),
            "k_cache": _w((lambda *s: torch.randn(*s, dtype=torch.bfloat16) * 0.8)(B, H, Sk, Dh)),
            "v_cache": _w((lambda *s: torch.randn(*s, dtype=torch.bfloat16) * 0.05)(B, H, Sk, Dh)),
            "wq": _w((lambda *s: torch.randn(*s, dtype=torch.bfloat16) * 0.8)(D, H * Dh) * (D ** -0.5)),
            "wo": _w((lambda *s: torch.randn(*s, dtype=torch.bfloat16) * 0.05)(H * Dh, D) * ((H * Dh) ** -0.5)),
        }
    _A_in = _A_setup()

    def _B_setup():
        B, Sq, D = 8, 304, 448
        H, Sk, Dh = 16, 1024, 256
        return {
            "x": _w((lambda *s: torch.randn(*s, dtype=torch.bfloat16) * 0.8)(B, Sq, D)),
            "k_cache": _w((lambda *s: torch.randn(*s, dtype=torch.bfloat16) * 0.8)(B, H, Sk, Dh)),
            "v_cache": _w((lambda *s: torch.randn(*s, dtype=torch.bfloat16) * 0.05)(B, H, Sk, Dh)),
            "wq": _w((lambda *s: torch.randn(*s, dtype=torch.bfloat16) * 0.8)(D, H * Dh) * (D ** -0.5)),
            "wo": _w((lambda *s: torch.randn(*s, dtype=torch.bfloat16) * 0.05)(H * Dh, D) * ((H * Dh) ** -0.5)),
        }
    _B_in = _B_setup()

    return {
        "A_x": _A_in["x"],
        "A_k_cache": _A_in["k_cache"],
        "A_v_cache": _A_in["v_cache"],
        "A_wq": _A_in["wq"],
        "A_wo": _A_in["wo"],
        "B_x": _B_in["x"],
        "B_k_cache": _B_in["k_cache"],
        "B_v_cache": _B_in["v_cache"],
        "B_wq": _B_in["wq"],
        "B_wo": _B_in["wo"],
    }

def reference(A_x, A_k_cache, A_v_cache, A_wq, A_wo, B_x, B_k_cache, B_v_cache, B_wq, B_wo):
    def _A_ref(x, k_cache, v_cache, wq, wo):
        B, Sq, D = x.shape
        H, Dh = 16, 256
        q = (lambda x, *d: x.permute(*d))((x @ wq).reshape(B, Sq, H, Dh), 0, 2, 1, 3)
        scores = torch.einsum("bhqd,bhkd->bhqk", q, k_cache) * (Dh ** -0.5)
        p = _softmax(scores, axis=-1)
        o = torch.einsum("bhqk,bhkd->bhqd", p, v_cache)
        return (lambda x, *d: x.permute(*d))(o, 0, 2, 1, 3).reshape(B, Sq, H * Dh) @ wo

    def _B_ref(x, k_cache, v_cache, wq, wo):
        B, Sq, D = x.shape
        H, Dh = 16, 256
        q = (lambda x, *d: x.permute(*d))((x @ wq).reshape(B, Sq, H, Dh), 0, 2, 1, 3)
        scores = torch.einsum("bhqd,bhkd->bhqk", q, k_cache) * (Dh ** -0.5)
        p = _softmax(scores, axis=-1)
        o = torch.einsum("bhqk,bhkd->bhqd", p, v_cache)
        return (lambda x, *d: x.permute(*d))(o, 0, 2, 1, 3).reshape(B, Sq, H * Dh) @ wo

    a = _A_ref(A_x, A_k_cache, A_v_cache, A_wq, A_wo)
    b = _B_ref(B_x, B_k_cache, B_v_cache, B_wq, B_wo)
    return torch.concatenate([a, b], axis=-1)
```

```cpp
#include <cuda_runtime.h>
#include <cuda_bf16.h>
#include <cuda.h>
#include <stdint.h>

#define REG_S "120"
#define REG_O "184"
#define ST_PIECES 4
#define NG 7

namespace {

constexpr int NB = 8, SQ = 304, DM = 448, NH = 16, SK = 1024, DH = 256;
constexpr int NQ = 152;
constexpr uint32_t GR = 16384;
constexpr uint32_t CH = NQ * 128;
constexpr uint32_t OFF_B = NG * GR;
constexpr uint32_t OFF_Q = OFF_B + 2 * CH;
constexpr uint32_t OFF_BAR = OFF_B + 6 * CH;
constexpr uint32_t BAR_FULL = OFF_BAR, BAR_EMPTY = OFF_BAR + 56;
constexpr uint32_t BAR_TFULL = OFF_BAR + 112;
constexpr uint32_t BAR_BEMPTY = OFF_BAR + 160;
constexpr uint32_t BAR_PUB = OFF_BAR + 208 - 16;
constexpr uint32_t BAR_SG = OFF_BAR + 240;
constexpr uint32_t BAR_PW = OFF_BAR + 288;
constexpr uint32_t BAR_LTOT = OFF_BAR + 304, BAR_LREADY = OFF_BAR + 312, BAR_STASH = OFF_BAR + 320, BAR_P2GO = OFF_BAR + 328;
constexpr uint32_t BAR_ST5 = OFF_BAR + 336, BAR_X4 = OFF_BAR + 344, BAR_SLOW = OFF_BAR + 352;
constexpr uint32_t OFF_FLAG = OFF_BAR + 360;
constexpr uint32_t OFF_L = OFF_BAR + 384;
constexpr uint32_t SMEM_USED = OFF_BAR + 1024;

struct Params {
  CUtensorMap x[2], k[2], v[2], wq[2], wo[2], out[2];
  const __nv_bfloat16* kp[2];
  const __nv_bfloat16* vp[2];
  const __nv_bfloat16* wqp[2];
  const __nv_bfloat16* wop[2];
  __nv_bfloat16* outp;
};

__device__ uint4 g_stash[128 * 4 * (CH / 16)];
__device__ unsigned g_zero_cnt[32];

#define TR(role, idx)
constexpr uint32_t SMEM_BYTES = SMEM_USED;

template <int TA>
__device__ __forceinline__ void wgmma_n152(float (&d)[76], uint64_t da, uint64_t db, int scale_d) {
  asm volatile("{\n.reg .pred p;\nsetp.ne.b32 p, %78, 0;\n"
    "wgmma.mma_async.sync.aligned.m64n152k16.f32.bf16.bf16 "
    "{%0, %1, %2, %3, %4, %5, %6, %7, %8, %9, %10, %11, %12, %13, %14, %15, "
    "%16, %17, %18, %19, %20, %21, %22, %23, %24, %25, %26, %27, %28, %29, %30, %31, "
    "%32, %33, %34, %35, %36, %37, %38, %39, %40, %41, %42, %43, %44, %45, %46, %47, "
    "%48, %49, %50, %51, %52, %53, %54, %55, %56, %57, %58, %59, %60, %61, %62, %63, "
    "%64, %65, %66, %67, %68, %69, %70, %71, %72, %73, %74, %75}, "
    "%76, %77, p, 1, 1, %79, 0;\n}\n"
    : "+f"(d[0]), "+f"(d[1]), "+f"(d[2]), "+f"(d[3]), "+f"(d[4]), "+f"(d[5]), "+f"(d[6]), "+f"(d[7]),
      "+f"(d[8]), "+f"(d[9]), "+f"(d[10]), "+f"(d[11]), "+f"(d[12]), "+f"(d[13]), "+f"(d[14]), "+f"(d[15]),
      "+f"(d[16]), "+f"(d[17]), "+f"(d[18]), "+f"(d[19]), "+f"(d[20]), "+f"(d[21]), "+f"(d[22]), "+f"(d[23]),
      "+f"(d[24]), "+f"(d[25]), "+f"(d[26]), "+f"(d[27]), "+f"(d[28]), "+f"(d[29]), "+f"(d[30]), "+f"(d[31]),
      "+f"(d[32]), "+f"(d[33]), "+f"(d[34]), "+f"(d[35]), "+f"(d[36]), "+f"(d[37]), "+f"(d[38]), "+f"(d[39]),
      "+f"(d[40]), "+f"(d[41]), "+f"(d[42]), "+f"(d[43]), "+f"(d[44]), "+f"(d[45]), "+f"(d[46]), "+f"(d[47]),
      "+f"(d[48]), "+f"(d[49]), "+f"(d[50]), "+f"(d[51]), "+f"(d[52]), "+f"(d[53]), "+f"(d[54]), "+f"(d[55]),
      "+f"(d[56]), "+f"(d[57]), "+f"(d[58]), "+f"(d[59]), "+f"(d[60]), "+f"(d[61]), "+f"(d[62]), "+f"(d[63]),
      "+f"(d[64]), "+f"(d[65]), "+f"(d[66]), "+f"(d[67]), "+f"(d[68]), "+f"(d[69]), "+f"(d[70]), "+f"(d[71]),
      "+f"(d[72]), "+f"(d[73]), "+f"(d[74]), "+f"(d[75])
    : "l"(da), "l"(db), "r"(scale_d), "n"(TA));
}

__device__ __forceinline__ void wg_fence() { asm volatile("wgmma.fence.sync.aligned;" ::: "memory"); }
__device__ __forceinline__ void wg_commit() { asm volatile("wgmma.commit_group.sync.aligned;" ::: "memory"); }
template <int N> __device__ __forceinline__ void wg_wait() { asm volatile("wgmma.wait_group.sync.aligned %0;" ::"n"(N) : "memory"); }
template <int N> __device__ __forceinline__ void fence_regs(float (&d)[N]) {
#pragma unroll
  for (int i = 0; i < N; i++) asm volatile("" : "+f"(d[i])::"memory");
}
template <uint32_t SBO> __device__ __forceinline__ uint64_t desc(uint32_t a16) {
  return (uint64_t)a16 | ((uint64_t)((SBO >> 4) | 0x40000000u) << 32);
}
__device__ __forceinline__ void mbar_init(uint32_t bar, uint32_t cnt) { asm volatile("mbarrier.init.shared::cta.b64 [%0], %1;" ::"r"(bar), "r"(cnt) : "memory"); }
__device__ __forceinline__ void mbar_expect(uint32_t bar, uint32_t bytes) { asm volatile("mbarrier.arrive.expect_tx.shared::cta.b64 _, [%0], %1;" ::"r"(bar), "r"(bytes) : "memory"); }
__device__ __forceinline__ void mbar_arrive(uint32_t bar, uint32_t cnt) { asm volatile("mbarrier.arrive.shared::cta.b64 _, [%0], %1;" ::"r"(bar), "r"(cnt) : "memory"); }
__device__ __forceinline__ void mbar_arrive_cluster(uint32_t bar, uint32_t cnt) { asm volatile("mbarrier.arrive.shared::cluster.b64 _, [%0], %1;" ::"r"(bar), "r"(cnt) : "memory"); }
__device__ __forceinline__ void mbar_arrive_if(bool c, uint32_t bar, uint32_t cnt) {
  asm volatile("{\n.reg .pred p;\nsetp.ne.u32 p, %2, 0;\n@p mbarrier.arrive.shared::cta.b64 _, [%0], %1;\n}" ::"r"(bar), "r"(cnt), "r"((uint32_t)c) : "memory");
}
__device__ __forceinline__ void mbar_arrive_cluster_if(bool c, uint32_t bar, uint32_t cnt) {
  asm volatile("{\n.reg .pred p;\nsetp.ne.u32 p, %2, 0;\n@p mbarrier.arrive.shared::cluster.b64 _, [%0], %1;\n}" ::"r"(bar), "r"(cnt), "r"((uint32_t)c) : "memory");
}
__device__ __forceinline__ uint32_t mbar_try(uint32_t bar, uint32_t parity) {
  uint32_t ok;
  asm volatile("{\n.reg .pred p;\nmbarrier.try_wait.parity.shared::cta.b64 p, [%1], %2;\nselp.u32 %0, 1, 0, p;\n}" : "=r"(ok) : "r"(bar), "r"(parity) : "memory");
  return ok;
}
__device__ __forceinline__ void mbar_wait(uint32_t bar, uint32_t parity) {
  asm volatile(
      "{\n.reg .pred p;\n.reg .u32 n;\n"
      "mbarrier.try_wait.parity.shared::cta.b64 p, [%0], %1;\n"
      "@p bra.uni DONE;\n"
      "mov.u32 n, 0;\n"
      "LOOP:\n"
      "mbarrier.try_wait.parity.shared::cta.b64 p, [%0], %1;\n"
      "@p bra.uni DONE;\n"
      "add.u32 n, n, 1;\n"
      "setp.lt.u32 p, n, 0x4000000;\n"
      "@p bra.uni LOOP;\n"
      "trap;\n"
      "DONE:\n}" ::"r"(bar), "r"(parity) : "memory");
}
__device__ __forceinline__ void fence_async_smem() { asm volatile("fence.proxy.async.shared::cta;" ::: "memory"); }
__device__ __forceinline__ void bar_sync(int id, int n) { asm volatile("bar.sync %0, %1;" ::"r"(id), "r"(n) : "memory"); }
#define ELECT "{\n.reg .pred e;\nelect.sync _|e, 0xffffffff;\n"
__device__ __forceinline__ void tma4_mc(uint32_t dst, const CUtensorMap* m, int c2, int c3, uint32_t bar, uint32_t bar_peer, uint64_t pol) {
  asm volatile(ELECT
               "@e cp.async.bulk.tensor.4d.shared::cluster.global.mbarrier::complete_tx::bytes.multicast::cluster.L2::cache_hint [%0], [%1, {%2, %2, %3, %4}], [%5], %6, %7;\n"
               "@e mbarrier.arrive.expect_tx.shared::cta.b64 _, [%5], 16384;\n"
               "@e mbarrier.arrive.expect_tx.shared::cluster.b64 _, [%8], 16384;\n}"
               ::"r"(dst), "l"(m), "r"(0), "r"(c2), "r"(c3), "r"(bar), "h"((uint16_t)3), "l"(pol), "r"(bar_peer) : "memory");
}
__device__ __forceinline__ void tma2(uint32_t dst, const CUtensorMap* m, int c0, int c1, uint32_t bar) {
  asm volatile(ELECT
               "@e cp.async.bulk.tensor.2d.shared::cluster.global.mbarrier::complete_tx::bytes [%0], [%1, {%2, %3}], [%4];\n"
               "@e mbarrier.arrive.expect_tx.shared::cta.b64 _, [%4], 19456;\n"
               "@e mbarrier.arrive.shared::cta.b64 _, [%4], 3;\n}"
               ::"r"(dst), "l"(m), "r"(c0), "r"(c1), "r"(bar) : "memory");
}
__device__ __forceinline__ void bulk_g2s(uint32_t dst, const void* src, uint32_t bar, uint64_t pol) {
  asm volatile(ELECT
               "@e cp.async.bulk.shared::cluster.global.mbarrier::complete_tx::bytes.L2::cache_hint [%0], [%1], 19456, [%2], %3;\n"
               "@e mbarrier.arrive.expect_tx.shared::cta.b64 _, [%2], 19456;\n"
               "@e mbarrier.arrive.shared::cta.b64 _, [%2], 3;\n}"
               ::"r"(dst), "l"(src), "r"(bar), "l"(pol) : "memory");
}
__device__ __forceinline__ void bulk_s2g(void* dst, uint32_t src, uint32_t bytes, uint64_t pol) {
  asm volatile(ELECT "@e cp.async.bulk.global.shared::cta.bulk_group.L2::cache_hint [%0], [%1], %2, %3;\n}" ::"l"(dst), "r"(src), "r"(bytes), "l"(pol) : "memory");
}
__device__ __forceinline__ void tma_red2(const CUtensorMap* m, int c0, int c1, uint32_t src) {
  asm volatile(ELECT "@e cp.reduce.async.bulk.tensor.2d.global.shared::cta.add.tile.bulk_group [%0, {%1, %2}], [%3];\n}" ::"l"(m), "r"(c0), "r"(c1), "r"(src) : "memory");
}
__device__ __forceinline__ void mbar_arrive_one(uint32_t bar, uint32_t cnt) {
  asm volatile(ELECT "@e mbarrier.arrive.shared::cta.b64 _, [%0], %1;\n}" ::"r"(bar), "r"(cnt) : "memory");
}
__device__ __forceinline__ void bulk_commit_wait_read() { asm volatile("cp.async.bulk.commit_group;\ncp.async.bulk.wait_group.read 0;" ::: "memory"); }
__device__ __forceinline__ void l2_prefetch_line(const void* p) { asm volatile("prefetch.global.L2 [%0];" ::"l"(p)); }
__device__ __forceinline__ uint32_t pack_bf16(float lo, float hi) {
  uint32_t r;
  asm("cvt.rn.bf16x2.f32 %0, %1, %2;" : "=r"(r) : "f"(hi), "f"(lo));
  return r;
}
__device__ __forceinline__ void stsm4t(uint32_t a, uint32_t r0, uint32_t r1, uint32_t r2, uint32_t r3) {
  asm volatile("stmatrix.sync.aligned.m8n8.x4.trans.shared.b16 [%0], {%1, %2, %3, %4};" ::"r"(a), "r"(r0), "r"(r1), "r"(r2), "r"(r3) : "memory");
}
__device__ __forceinline__ void stsm2t(uint32_t a, uint32_t r0, uint32_t r1) {
  asm volatile("stmatrix.sync.aligned.m8n8.x2.trans.shared.b16 [%0], {%1, %2};" ::"r"(a), "r"(r0), "r"(r1) : "memory");
}
__device__ __forceinline__ float ex2(float x) { float y; asm("ex2.approx.ftz.f32 %0, %1;" : "=f"(y) : "f"(x)); return y; }
__device__ __forceinline__ float2 lds64f(uint32_t a) { float2 v; asm volatile("ld.shared.v2.f32 {%0, %1}, [%2];" : "=f"(v.x), "=f"(v.y) : "r"(a) : "memory"); return v; }

template <int G0, int G1, bool SCALE>
__device__ __forceinline__ void store_tile_T(const float (&d)[76], uint32_t a, float c) {
#pragma unroll
  for (int g = G0; g < G1; g++) {
    float v[8];
#pragma unroll
    for (int i = 0; i < 8; i++) v[i] = 8 * g + i < 76 ? (SCALE ? d[8 * g + i] * c : d[8 * g + i]) : 0.f;
    if (g < 9) stsm4t(a + g * 2048, pack_bf16(v[0], v[1]), pack_bf16(v[2], v[3]), pack_bf16(v[4], v[5]), pack_bf16(v[6], v[7]));
    else stsm2t(a + g * 2048, pack_bf16(v[0], v[1]), pack_bf16(v[2], v[3]));
  }
}
__device__ __forceinline__ void store_tile_T_scaled(const float (&d)[76], uint32_t a, uint32_t linv, float2 (&sc)[19], bool on) {
#pragma unroll
  for (int g = 0; g < 6; g++) sc[g] = lds64f(linv + g * 32);
#pragma unroll
  for (int g = 0; g < 9; g++) {
    const float2 s0 = sc[2 * g], s1 = sc[2 * g + 1];
    const uint32_t r0 = pack_bf16(d[8 * g] * s0.x, d[8 * g + 1] * s0.y), r1 = pack_bf16(d[8 * g + 2] * s0.x, d[8 * g + 3] * s0.y);
    const uint32_t r2 = pack_bf16(d[8 * g + 4] * s1.x, d[8 * g + 5] * s1.y), r3 = pack_bf16(d[8 * g + 6] * s1.x, d[8 * g + 7] * s1.y);
    if (2 * g + 6 < 19) sc[2 * g + 6] = lds64f(linv + (2 * g + 6) * 32);
    if (2 * g + 7 < 19) sc[2 * g + 7] = lds64f(linv + (2 * g + 7) * 32);
    asm volatile("{\n.reg .pred p;\nsetp.ne.u32 p, %5, 0;\n@p stmatrix.sync.aligned.m8n8.x4.trans.shared.b16 [%0], {%1, %2, %3, %4};\n}"
                 ::"r"(a + g * 2048), "r"(r0), "r"(r1), "r"(r2), "r"(r3), "r"((uint32_t)on) : "memory");
  }
  asm volatile("{\n.reg .pred p;\nsetp.ne.u32 p, %3, 0;\n@p stmatrix.sync.aligned.m8n8.x2.trans.shared.b16 [%0], {%1, %2};\n}"
               ::"r"(a + 9 * 2048), "r"(pack_bf16(d[72] * sc[18].x, d[73] * sc[18].y)), "r"(pack_bf16(d[74] * sc[18].x, d[75] * sc[18].y)), "r"((uint32_t)on) : "memory");
}
__device__ __forceinline__ float rcp(float x) { float y; asm("rcp.approx.ftz.f32 %0, %1;" : "=f"(y) : "f"(x)); return y; }
__device__ __forceinline__ uint4 lds128(uint32_t a) {
  uint4 v;
  asm volatile("ld.shared.v4.u32 {%0, %1, %2, %3}, [%4];" : "=r"(v.x), "=r"(v.y), "=r"(v.z), "=r"(v.w) : "r"(a) : "memory");
  return v;
}
__device__ __forceinline__ float sum8(uint4 v) {
  return ((__uint_as_float(v.x << 16) + __uint_as_float(v.x & 0xffff0000u)) + (__uint_as_float(v.y << 16) + __uint_as_float(v.y & 0xffff0000u))) +
         ((__uint_as_float(v.z << 16) + __uint_as_float(v.z & 0xffff0000u)) + (__uint_as_float(v.w << 16) + __uint_as_float(v.w & 0xffff0000u)));
}
__device__ __forceinline__ void mma_chunk(float (&d)[76], uint32_t a, uint32_t b, int acc) {
  wg_fence();
#pragma unroll
  for (int ks = 0; ks < 4; ks++) wgmma_n152<1>(d, desc<2048>(a + ks * 256), desc<1024>(b + ks * 2), ks == 0 ? acc : 1);
}

constexpr float SCALE_LOG2E = 0.0625f * 1.4426950408889634f;

__device__ __forceinline__ void slow_path(uint32_t qbuf, const __nv_bfloat16* kp, const __nv_bfloat16* vp, int warp, int lane) {
#pragma unroll 1
  for (int r = warp; r < NQ; r += 4) {
    uint32_t a = qbuf + (lane >> 3) * CH + r * 128 + (((lane & 7) ^ (r & 7)) << 4);
    uint32_t qv[4];
    asm volatile("ld.shared.v4.u32 {%0, %1, %2, %3}, [%4];" : "=r"(qv[0]), "=r"(qv[1]), "=r"(qv[2]), "=r"(qv[3]) : "r"(a) : "memory");
    float q[8], o[8];
#pragma unroll
    for (int i = 0; i < 4; i++) { q[2 * i] = __uint_as_float(qv[i] << 16); q[2 * i + 1] = __uint_as_float(qv[i] & 0xffff0000u); }
#pragma unroll
    for (int i = 0; i < 8; i++) o[i] = 0.f;
    float m = -INFINITY, l = 0.f;
#pragma unroll 2
    for (int t = 0; t < SK; t++) {
      uint4 kv = __ldg(reinterpret_cast<const uint4*>(kp + (size_t)t * DH) + lane);
      uint4 vv = __ldg(reinterpret_cast<const uint4*>(vp + (size_t)t * DH) + lane);
      uint32_t kw[4] = {kv.x, kv.y, kv.z, kv.w}, vw[4] = {vv.x, vv.y, vv.z, vv.w};
      float s = 0.f;
#pragma unroll
      for (int i = 0; i < 4; i++) s = fmaf(q[2 * i], __uint_as_float(kw[i] << 16), fmaf(q[2 * i + 1], __uint_as_float(kw[i] & 0xffff0000u), s));
#pragma unroll
      for (int x = 16; x > 0; x >>= 1) s += __shfl_xor_sync(0xffffffffu, s, x);
      float mn = fmaxf(m, s);
      float corr = (m == mn) ? 1.f : exp2f(m - mn), p = exp2f(s - mn);
      m = mn;
      l = l * corr + p;
#pragma unroll
      for (int i = 0; i < 4; i++) {
        o[2 * i] = fmaf(p, __uint_as_float(vw[i] << 16), o[2 * i] * corr);
        o[2 * i + 1] = fmaf(p, __uint_as_float(vw[i] & 0xffff0000u), o[2 * i + 1] * corr);
      }
    }
    float inv = 1.f / l;
    asm volatile("st.shared.v4.u32 [%0], {%1, %2, %3, %4};" ::"r"(a), "r"(pack_bf16(o[0] * inv, o[1] * inv)), "r"(pack_bf16(o[2] * inv, o[3] * inv)),
                 "r"(pack_bf16(o[4] * inv, o[5] * inv)), "r"(pack_bf16(o[6] * inv, o[7] * inv)) : "memory");
  }
}

__global__ void __cluster_dims__(2, 1, 1) __launch_bounds__(512, 1) fused_mha_kernel(const __grid_constant__ Params p) {
  extern __shared__ __align__(1024) uint8_t smem_raw[];
  const uint32_t sb = __shfl_sync(0xffffffffu, (uint32_t)__cvta_generic_to_shared(smem_raw), 0);
  const int wg = __shfl_sync(0xffffffffu, (int)(threadIdx.x >> 7), 0);
  const int warp = __shfl_sync(0xffffffffu, (int)((threadIdx.x >> 5) & 3), 0);
  const int lane = __shfl_sync(0xffffffffu, (int)(threadIdx.x & 31), threadIdx.x & 31);
  if (threadIdx.x == 0) {
    if (sb & 1023) asm volatile("trap;");
    for (int i = 0; i < NG; i++) { mbar_init(sb + BAR_FULL + 8 * i, 1); mbar_init(sb + BAR_EMPTY + 8 * i, 4); }
    for (int i = 0; i < 6; i++) { mbar_init(sb + BAR_TFULL + 8 * i, 4); mbar_init(sb + BAR_BEMPTY + 8 * i, 6); mbar_init(sb + BAR_SG + 8 * i, 4); }
    for (int i = 2; i < 6; i++) mbar_init(sb + BAR_PUB + 8 * i, 4);
    mbar_init(sb + BAR_PW, 4); mbar_init(sb + BAR_PW + 8, 4);
    mbar_init(sb + BAR_LTOT, 8); mbar_init(sb + BAR_LREADY, 4); mbar_init(sb + BAR_STASH, 1); mbar_init(sb + BAR_P2GO, 2);
    mbar_init(sb + BAR_ST5, 1); mbar_init(sb + BAR_X4, 2); mbar_init(sb + BAR_SLOW, 4);
    asm volatile("st.shared.u32 [%0], %1;" ::"r"(sb + OFF_FLAG), "r"(0) : "memory");
    asm volatile("fence.mbarrier_init.release.cluster;" ::: "memory");
  }
  asm volatile("barrier.cluster.arrive.release.aligned;\nbarrier.cluster.wait.acquire.aligned;" ::: "memory");

  if (wg == 0) {
    asm volatile("setmaxnreg.dec.sync.aligned.u32 24;");
    int cta;
    asm volatile("mov.u32 %0, %%ctaid.x;" : "=r"(cta));
    const int rank = cta & 1, br = cta >> 6, b = (cta >> 3) & 7, hg = (cta >> 1) & 3;
    const int xrow = b * SQ + rank * NQ;
    char* stash = reinterpret_cast<char*>(g_stash) + (size_t)cta * (4 * CH);
    uint64_t pol_first, pol_normal;
    asm volatile("createpolicy.fractional.L2::evict_first.b64 %0, 1.0;" : "=l"(pol_first));
    asm volatile("createpolicy.fractional.L2::evict_normal.b64 %0, 1.0;" : "=l"(pol_normal));
    auto load_x = [&](uint32_t u, int c) { tma2(sb + OFF_B + u * CH, &p.x[br], c * 64, xrow, sb + BAR_TFULL + 8 * u); };
    if (warp == 0) {
      uint32_t full_peer;
      asm volatile("mapa.shared::cluster.u32 %0, %1, %2;" : "=r"(full_peer) : "r"(sb + BAR_FULL), "r"(rank ^ 1));
      int m = rank, rnd = 0;
      uint32_t slot = rank, k = 0;
#pragma unroll 1
      for (int n = rank; n < 376; n += 2) {
        const CUtensorMap* map;
        int c2, c3;
        uint64_t pol = pol_normal;
        if (m < 156) {
          const int hb = m >= 78, g = m - hb * 78, h = hg * 4 + rnd * 2 + hb;
          if (g < 14) {
            map = &p.wq[br];
            c2 = h * 4 + (g < 10 ? g & 1 : (g - 10) >> 1) * 2;
            c3 = (g < 10 ? g >> 1 : 5 + (g & 1)) * 8;
          } else {
            const int it = (g - 14) >> 1;
            const bool isv = it == 31 || (it > 0 && !(it & 1));
            map = isv ? &p.v[br] : &p.k[br];
            c2 = (g & 1) * 2;
            c3 = (b * NH + h) * (SK / 8) + (isv ? (it - 1) >> 1 : (it + 1) >> 1) * 8;
            pol = pol_first;
          }
        } else {
          const int g = m - 156;
          int kc;
          if (g < 16) {
            const int c = g < 12 ? g >> 1 : 6 + (g & 1);
            kc = (0x76325410 >> (c * 4)) & 7;
            c2 = (g < 12 ? g & 1 : g < 14) * 2;
          } else {
            kc = (0x32104765 >> (((g - 16) >> 1) * 4)) & 7;
            c2 = 4 + (g & 1) * 2;
          }
          map = &p.wo[br];
          c3 = (hg * 4 + rnd * 2) * 32 + kc * 8;
        }
        if (k > 0) mbar_wait(sb + BAR_EMPTY + 8 * slot, (NG & 1) ? ((k - 1) >> 1) & 1 : (k - 1) & 1);
        tma4_mc(sb + slot * GR, map, c2, c3, sb + BAR_FULL + 8 * slot, full_peer + 8 * slot, pol);
        TR(0, n >> 1);
        slot += 2;
        if (slot >= NG) { slot -= NG; k++; }
        m += 2;
        if (m >= 188) { m -= 188; rnd++; }
      }
    } else if (warp == 1) {
#pragma unroll 1
      for (uint32_t u = 2; u < 5; u++) load_x(u, u);
#pragma unroll 1
      for (int rnd = 0; rnd < 2; rnd++) {
        mbar_wait(sb + BAR_LREADY, 0);
#pragma unroll 1
        for (uint32_t u = 2; u < 6; u++) {
          mbar_wait(sb + BAR_PUB + 8 * u, 1);
#pragma unroll 1
          for (uint32_t o = 0; o < CH; o += CH / ST_PIECES) {
            bulk_s2g(stash + (u - 2) * CH + o, sb + OFF_B + u * CH + o, CH / ST_PIECES, pol_normal);
            bulk_commit_wait_read();
          }
          if (u < 5) load_x(u, u);
          else mbar_arrive_one(sb + BAR_ST5, 1);
        }
        asm volatile("cp.async.bulk.wait_group 0;\nfence.proxy.async;" ::: "memory");
        mbar_arrive_one(sb + BAR_STASH, 1);
        mbar_wait(sb + BAR_LREADY, 1);
#pragma unroll 1
        for (uint32_t i = 0; i < 4; i++) {
          const uint32_t u = 2 + ((i + 1) & 3);
          mbar_wait(sb + BAR_BEMPTY + 8 * u, 0);
          bulk_g2s(sb + OFF_B + u * CH, stash + i * CH, sb + BAR_TFULL + 8 * u, pol_normal);
        }
        if (rnd == 0) { mbar_wait(sb + BAR_BEMPTY + 16, 1); load_x(2, 2); }
      }
    } else if (warp == 2) {
#pragma unroll 1
      for (int ph = 0; ph < 6; ph++) {
        const bool isP = ph == 2 || ph == 5;
        if (ph == 3) {
          mbar_wait(sb + BAR_BEMPTY, 1); mbar_wait(sb + BAR_BEMPTY + 8, 1);
          mbar_wait(sb + BAR_BEMPTY, 0); mbar_wait(sb + BAR_BEMPTY + 8, 0);
        } else if (ph > 0) {
          mbar_wait(sb + BAR_LTOT, isP);
        }
        if (isP) { mbar_wait(sb + BAR_STASH, ph & 1); asm volatile("fence.proxy.async;" ::: "memory"); }
#pragma unroll 1
        for (uint32_t i = 0; i < 4; i++) {
          const uint32_t u = i & 1;
          mbar_wait(sb + BAR_BEMPTY + 8 * u, i < 2);
          if (isP) bulk_g2s(sb + OFF_B + u * CH, stash + i * CH, sb + BAR_TFULL + 8 * u, pol_normal);
          else load_x(u, i < 2 ? i : i + 3);
        }
        if (!isP && ph < 4) {
          const char* q = reinterpret_cast<const char*>(p.wqp[br]) + (size_t)((b * 2 + rank) * 28) * (NH * DH * 2) + (hg * 4 + (ph == 3 ? 3 : ph + 1)) * 512;
#pragma unroll 1
          for (int line = lane; line < 112; line += 32) l2_prefetch_line(q + (size_t)(line >> 2) * (NH * DH * 2) + (line & 3) * 128);
        }
        if (ph == 1 || ph == 4) {
          const char* q = reinterpret_cast<const char*>(p.wop[br]) + (size_t)(hg * 1024 + (ph >> 2) * 512 + (b * 2 + rank) * 32) * (DM * 2) + lane * 128;
#pragma unroll 1
          for (int i = 0; i < 7; i++) l2_prefetch_line(q + i * 4096);
        }
      }
    } else {
      mbar_wait(sb + BAR_PUB + 40, 0);
      {
        char* o = reinterpret_cast<char*>(p.outp) + (size_t)(xrow + hg * 38) * (2 * DM * 2) + br * (DM * 2) + lane * 16;
#pragma unroll 1
        for (int i = 0; i < 38; i++) {
          *reinterpret_cast<uint4*>(o) = make_uint4(0, 0, 0, 0);
          if (lane < 24) *reinterpret_cast<uint4*>(o + 512) = make_uint4(0, 0, 0, 0);
          o += 2 * DM * 2;
          __nanosleep(200);
        }
      }
      asm volatile("fence.proxy.async;" ::: "memory");
      __threadfence();
      __syncwarp();
      unsigned* cnt = &g_zero_cnt[(cta >> 3) * 2 + rank];
      unsigned target = 0;
      if (lane == 0) target = (atomicAdd(cnt, 1) & ~3u) + 4;
      target = __shfl_sync(0xffffffffu, target, 0);
      mbar_wait(sb + BAR_STASH, 0);
#pragma unroll 1
      for (unsigned n = 0;; n++) {
        unsigned v;
        asm volatile("ld.acquire.gpu.global.u32 %0, [%1];" : "=r"(v) : "l"(cnt) : "memory");
        if ((int)(v - target) >= 0) break;
        if (n > (1u << 24)) asm volatile("trap;");
      }
      asm volatile("fence.proxy.async;" ::: "memory");
      __syncwarp();
#pragma unroll 1
      for (int i = 0; i < 14; i++) {
        const int rnd = i >= 7, q = i - rnd * 7;
        const uint32_t u = q < 4 ? q & 1 : q - 1;
        const int t = q < 4 ? q ^ 2 : q;
        mbar_wait(sb + BAR_SG + 8 * u, q < 4 ? q >> 1 : rnd);
#pragma unroll 1
        for (int g = 0; g < 4; g++) {
          tma_red2(&p.out[g == 3], br * DM + t * 64, xrow + g * 40, sb + OFF_B + u * CH + g * 5120);
          if (i < 11) bulk_commit_wait_read();
        }
        if (q < 4) mbar_arrive_one(sb + BAR_BEMPTY + 8 * u, 6);
        else if (rnd == 0) {
          if (u < 5) load_x(u, u);
          else mbar_arrive_one(sb + BAR_ST5, 1);
        }
      }
      asm volatile("cp.async.bulk.commit_group;\ncp.async.bulk.wait_group 0;" ::: "memory");
      TR(0, 200);
    }
  } else {
    uint32_t empty0, empty1;
    asm volatile("mapa.shared::cluster.u32 %0, %1, 0;" : "=r"(empty0) : "r"(sb + BAR_EMPTY));
    asm volatile("mapa.shared::cluster.u32 %0, %1, 1;" : "=r"(empty1) : "r"(sb + BAR_EMPTY));
    const bool sig = warp == 0 && lane == 0;
    const uint32_t sd = (sb & 0x3FFFF) >> 4;
    const uint32_t st_off = (lane >> 4) * 1024 + (lane & 7) * 128 + (((2 * warp + ((lane >> 3) & 1)) ^ (lane & 7)) << 4);
    auto wrap = [](uint32_t q) { return q >= 2 * NG ? q - 2 * NG : q; };
    auto acquire = [&](uint32_t n, int k) {
      const uint32_t q = wrap(n + k), slot = q >= NG ? q - NG : q;
      mbar_wait(sb + BAR_FULL + 8 * slot, q >= NG);
      return sd + slot * (GR / 16);
    };
    auto release = [&](uint32_t n, int k, uint32_t cnt) {
      const uint32_t q = wrap(n + (k < 0 ? k + 2 * NG : k)), slot = q >= NG ? q - NG : q;
      mbar_arrive_cluster_if(sig, (((q + NG) & 1) ? empty1 : empty0) + 8 * slot, cnt);
    };
    auto releaseB = [&](uint32_t u, uint32_t cnt) { mbar_arrive_if(sig, sb + BAR_BEMPTY + 8 * u, cnt); };
    auto publish = [&](uint32_t bar) {
      fence_async_smem();
      __syncwarp();
      mbar_arrive_if(lane == 0, bar, 1);
    };
    const uint32_t bd = sd + OFF_B / 16;
    if (wg == 1) {
      asm volatile("setmaxnreg.dec.sync.aligned.u32 " REG_S ";");
      float s[76];
#pragma unroll
      for (int i = 0; i < 76; i++) s[i] = 0.f;
      fence_regs(s);
      auto qk = [&](uint32_t a, int half, int k0, int k1) {
        const uint32_t bq = bd + (a >> 20);
        wg_fence();
#pragma unroll
        for (int ks = k0; ks < k1; ks++)
          wgmma_n152<0>(s, desc<2048>(a + (ks >> 2) * 64 + (ks & 3) * 2), desc<1024>(bq + (2 + half * 2 + (ks >> 2)) * (CH / 16) + (ks & 3) * 2), half + ks != 0);
      };
      auto softmax = [&](uint32_t pa) {
#pragma unroll
        for (int g = 0; g < 9; g++)
          stsm4t(pa + g * 2048, pack_bf16(ex2(s[8 * g]), ex2(s[8 * g + 1])), pack_bf16(ex2(s[8 * g + 2]), ex2(s[8 * g + 3])),
                 pack_bf16(ex2(s[8 * g + 4]), ex2(s[8 * g + 5])), pack_bf16(ex2(s[8 * g + 6]), ex2(s[8 * g + 7])));
        stsm2t(pa + 9 * 2048, pack_bf16(ex2(s[72]), ex2(s[73])), pack_bf16(ex2(s[74]), ex2(s[75])));
      };
#pragma unroll 1
      for (int hh = 0; hh < 4; hh++) {
        uint32_t n = hh == 0 ? 14 % (2 * NG) : hh == 1 ? 92 % (2 * NG) : hh == 2 ? 202 % (2 * NG) : 280 % (2 * NG);
        {
          mbar_wait(sb + BAR_PUB + 16, 0);
          mbar_wait(sb + BAR_PUB + 24, 0);
          uint32_t a = acquire(n, 0);
          TR(1, (hh * 16) * 4);
          qk(a, 0, 0, 8);
          wg_commit();
          a = acquire(n, 1);
          mbar_wait(sb + BAR_PUB + 32, 0);
          mbar_wait(sb + BAR_PUB + 40, 0);
          qk(a, 1, 0, 8);
          wg_commit();
          wg_wait<1>();
          release(n, 0, 2);
          mbar_wait(sb + BAR_BEMPTY, 1);
          TR(1, (hh * 16) * 4 + 1);
        }
#pragma unroll 1
        for (int j = 0; j < 15; j++) {
          wg_wait<0>();
          fence_regs(s);
          TR(1, (hh * 16 + j) * 4 + 2);
          release(n, 1, 2);
          n = wrap(n + (j > 0 ? 4 : 2));
          softmax(sb + OFF_B + (j & 1) * CH + st_off);
          TR(1, (hh * 16 + j) * 4 + 3);
          uint32_t a = acquire(n, 0);
          TR(1, (hh * 16 + j + 1) * 4);
          qk(a, 0, 0, 4);
          __syncwarp();
          mbar_arrive_if(lane == 0, sb + BAR_PW + 8 * (j & 1), 1);
          qk(a, 0, 4, 8);
          wg_commit();
          a = acquire(n, 1);
          qk(a, 1, 0, 8);
          wg_commit();
          publish(sb + BAR_TFULL + 8 * (j & 1));
          wg_wait<1>();
          release(n, 0, 2);
          mbar_wait(sb + BAR_BEMPTY + 8 * ((j + 1) & 1), (((j + 1) >> 1) + 1) & 1);
          TR(1, (hh * 16 + j + 1) * 4 + 1);
        }
        wg_wait<0>();
        fence_regs(s);
        TR(1, (hh * 16 + 15) * 4 + 2);
        release(n, 1, 2);
        softmax(sb + OFF_B + CH + st_off);
        publish(sb + BAR_TFULL + 8);
        mbar_arrive_if(lane == 0, sb + BAR_PW + 8, 1);
        TR(1, (hh * 16 + 15) * 4 + 3);
        mbar_wait(sb + BAR_LTOT, hh & 1);
        bar_sync(1, 128);
        int bad;
        {
          const uint32_t a = sb + OFF_B + CH + warp * (38 * 128) + lane * 16;
          uint4 v[10];
#pragma unroll
          for (int i = 0; i < 10; i++) v[i] = lds128(a + i * 512);
          float t[10];
#pragma unroll
          for (int i = 0; i < 10; i++) t[i] = sum8(v[i]);
          const bool b0 = lane & 1, b1 = lane & 2, b2 = lane & 4;
          float x[5];
#pragma unroll
          for (int i = 0; i < 5; i++) x[i] = (b0 ? t[2 * i + 1] : t[2 * i]) + __shfl_xor_sync(0xffffffffu, b0 ? t[2 * i] : t[2 * i + 1], 1);
          const float y0 = (b1 ? x[1] : x[0]) + __shfl_xor_sync(0xffffffffu, b1 ? x[0] : x[1], 2);
          const float y1 = (b1 ? x[3] : x[2]) + __shfl_xor_sync(0xffffffffu, b1 ? x[2] : x[3], 2);
          const float y2 = x[4] + __shfl_xor_sync(0xffffffffu, x[4], 2);
          float t0 = (b2 ? y1 : y0) + __shfl_xor_sync(0xffffffffu, b2 ? y0 : y1, 4);
          float t1 = y2 + __shfl_xor_sync(0xffffffffu, y2, 4);
          const int r0 = (lane & 7) * 4 + (lane >> 3), r1 = 32 + (lane & 1) * 4 + (lane >> 3);
          const bool has1 = (lane & 6) == 0 && r1 < 38;
          const uint32_t la = sb + OFF_L + warp * (38 * 4);
          float u0, u1 = 1.f;
          asm volatile("ld.shared.f32 %0, [%1];" : "=f"(u0) : "r"(la + r0 * 4) : "memory");
          if (has1) asm volatile("ld.shared.f32 %0, [%1];" : "=f"(u1) : "r"(la + r1 * 4) : "memory");
          t0 += u0;
          t1 = has1 ? t1 + u1 : 1.f;
          bad = !(t0 > 0x1p-60f && t0 < 0x1p60f && t1 > 0x1p-60f && t1 < 0x1p60f);
          asm volatile("st.shared.f32 [%0], %1;" ::"r"(la + r0 * 4), "f"(rcp(t0)) : "memory");
          if (has1) asm volatile("st.shared.f32 [%0], %1;" ::"r"(la + r1 * 4), "f"(rcp(t1)) : "memory");
          if (bad) asm volatile("st.shared.u32 [%0], %1;" ::"r"(sb + OFF_FLAG), "r"(hh + 1) : "memory");
        }
        __syncwarp();
        mbar_arrive_if(lane == 0, sb + BAR_LREADY, 1);
        TR(1, 256 + hh);
        asm volatile("{\n.reg .pred p, q;\nsetp.ne.b32 p, %0, 0;\nbar.red.or.pred q, 1, 128, p;\nselp.b32 %0, 1, 0, q;\n}" : "+r"(bad)::"memory");
        if (__shfl_sync(0xffffffffu, bad, 0)) {
          int cta;
          asm volatile("mov.u32 %0, %%ctaid.x;" : "=r"(cta));
          const size_t off = (size_t)(((cta >> 1) & 31) * 4 + hh) * (SK * DH);
          slow_path(sb + OFF_Q, p.kp[cta >> 6] + off, p.vp[cta >> 6] + off, warp, lane);
          publish(sb + BAR_SLOW);
        }
        __syncwarp();
#pragma unroll 1
        for (uint32_t u = 2; u < 6; u++) mbar_wait(sb + BAR_PUB + 8 * u, 1);
        if (hh & 1) {
          const uint32_t rnd = hh >> 1;
#pragma unroll
          for (int i = 0; i < 76; i++) s[i] = 0.f;
          fence_regs(s);
          mbar_wait(sb + BAR_P2GO, rnd);
          n = rnd ? 361 % (2 * NG) : 173 % (2 * NG);
#pragma unroll 1
          for (uint32_t i = 0; i < 8; i++) {
            const uint32_t u = 2 + ((i + 1) & 3);
            if (i >= 4) mbar_wait(sb + BAR_TFULL + 8 * u, rnd);
            const uint32_t a = acquire(n, 0);
            mma_chunk(s, a, bd + u * (CH / 16), 1);
            wg_commit();
            wg_wait<1>();
            if (i > 0) { release(n, -2, 2); releaseB(2 + (i & 3), 2); }
            n = wrap(n + 2);
          }
          mbar_wait(sb + BAR_BEMPTY + 40, 1);
          wg_wait<0>();
          fence_regs(s);
          release(n, -2, 2);
          releaseB(2, 2);
          store_tile_T<0, 10, false>(s, sb + OFF_B + 5 * CH + st_off, 1.f);
          publish(sb + BAR_SG + 40);
        }
      }
    } else {
      asm volatile("setmaxnreg.inc.sync.aligned.u32 " REG_O ";");
      const int w = wg - 2;
      float dA[76], dB[76];
#pragma unroll
      for (int i = 0; i < 76; i++) { dA[i] = 0.f; dB[i] = 0.f; }
      fence_regs(dA);
      fence_regs(dB);
      uint32_t n = 0, skip = 1, nslow = 0;
      const uint32_t linv = sb + OFF_L + (lane & 3) * 8;
#pragma unroll 1
      for (int ph = 0;; ph++) {
        const bool isP = ph == 2 || ph == 5;
        {
          mbar_wait(sb + BAR_TFULL, 0);
          uint32_t a = acquire(n, 0);
          TR(wg, ph * 64);
          mma_chunk(dA, a + w * 64, bd, 0);
          wg_commit();
          if (ph != 0 && ph != 3) publish(sb + BAR_PUB + 8 * (2 + w));
          wg_wait<1>();
          fence_regs(dB);
          if (ph == 3) {
            release(n, -2, 1);
            releaseB(2, 2);
            mbar_wait(sb + BAR_BEMPTY + 8 * (3 + w), 1);
          }
          if (!skip) store_tile_T<0, 10, false>(dB, sb + OFF_B + ((ph == 3 ? 3 : 4) + w) * CH + st_off, 1.f);
          TR(wg, ph * 64 + 62);
          a = acquire(n, 1);
          mma_chunk(dB, a + w * 64, bd, 0);
          wg_commit();
          if (ph != 0) publish(sb + (ph == 3 ? BAR_SG + 8 * (3 + w) : BAR_PUB + 8 * (4 + w)));
          wg_wait<1>();
          release(n, 0, 1);
          TR(wg, ph * 64 + 1);
          n = wrap(n + 2);
        }
        const uint32_t cend = isP ? 6 : 5;
#pragma unroll 1
        for (uint32_t c = 1; c < cend; c++) {
          const uint32_t u = isP ? c & 3 : c, pu = isP ? (c - 1) & 3 : c - 1;
          if (u < 2) mbar_wait(sb + BAR_TFULL + 8 * u, c >> 2);
          else mbar_wait(sb + (isP ? BAR_PUB : BAR_TFULL) + 8 * u, isP ? 1 : ph & 1);
          uint32_t a = acquire(n, 0);
          TR(wg, ph * 64 + c * 2);
          mma_chunk(dA, a + w * 64, bd + u * (CH / 16), 1);
          wg_commit();
          wg_wait<1>();
          release(n, -1, 1);
          mbar_arrive_if(sig && pu < 2, sb + BAR_BEMPTY + 8 * pu, 3);
          a = acquire(n, 1);
          mma_chunk(dB, a + w * 64, bd + u * (CH / 16), 1);
          wg_commit();
          wg_wait<1>();
          release(n, 0, 1);
          TR(wg, ph * 64 + c * 2 + 1);
          n = wrap(n + 2);
        }
        if (!isP) {
          const int hh = ph - (ph >= 3);
          mbar_wait(sb + BAR_TFULL, 1);
          uint32_t a = acquire(n, 0);
          TR(wg, ph * 64 + 10);
          mma_chunk(dA, a + w * 64, bd, 1);
          wg_commit();
          wg_wait<1>();
          release(n, -1, 1);
          mbar_arrive_if(sig, sb + BAR_X4, 1);
          mbar_wait(sb + BAR_TFULL + 8, 1);
          a = acquire(n, 1);
          mma_chunk(dA, a + w * 64, bd + CH / 16, 1);
          wg_commit();
          wg_wait<1>();
          release(n, 0, 1);
          a = acquire(n, 2);
          TR(wg, ph * 64 + 12);
          mma_chunk(dB, a + w * 64, bd, 1);
          wg_commit();
          mbar_wait(sb + BAR_X4, hh & 1);
          a = acquire(n, 3);
          wg_wait<1>();
          fence_regs(dA);
          release(n, 1, 1);
          TR(wg, ph * 64 + 14);
          store_tile_T<0, 4, true>(dA, sb + OFF_Q + w * CH + st_off, SCALE_LOG2E);
          mma_chunk(dB, a + w * 64, bd + CH / 16, 1);
          wg_commit();
          store_tile_T<4, 10, true>(dA, sb + OFF_Q + w * CH + st_off, SCALE_LOG2E);
          publish(sb + BAR_PUB + 8 * (2 + w));
          TR(wg, ph * 64 + 13);
          if (hh > 0) mbar_wait(sb + BAR_ST5, (hh & 1) ^ 1);
          wg_wait<0>();
          fence_regs(dB);
          release(n, 2, 1);
          release(n, 3, 1);
          releaseB(0, 3);
          releaseB(1, 3);
          store_tile_T<0, 10, true>(dB, sb + OFF_Q + (2 + w) * CH + st_off, SCALE_LOG2E);
          publish(sb + BAR_PUB + 8 * (4 + w));
          TR(wg, ph * 64 + 15);
          n = wrap(n + 8);
          float l[5] = {0.f, 0.f, 0.f, 0.f, 0.f};
#pragma unroll 1
          for (int j = 0; j < 15; j++) {
            mbar_wait(sb + BAR_PW + 8 * (j & 1), (j >> 1) & 1);
            {
              const uint32_t ra = sb + OFF_B + (j & 1) * CH + (w * 4 + warp) * (19 * 128) + lane * 16;
              uint4 v0 = lds128(ra), v1 = lds128(ra + 512), v2 = lds128(ra + 1024);
              l[0] += sum8(v0);
              v0 = lds128(ra + 1536);
              l[1] += sum8(v1);
              v1 = lds128(ra + 2048);
              l[2] += sum8(v2);
              l[3] += sum8(v0);
              l[4] += sum8(v1);
            }
            const uint32_t a0 = acquire(n, 0);
            mbar_wait(sb + BAR_TFULL + 8 * (j & 1), (j >> 1) & 1);
            TR(wg, ph * 64 + 16 + j * 2);
            const uint32_t bb = bd + (j & 1) * (CH / 16);
            mma_chunk(dA, a0 + w * 64, bb, j > 0);
            wg_commit();
            const uint32_t a1 = acquire(n, 1);
            mma_chunk(dB, a1 + w * 64, bb, j > 0);
            wg_commit();
            wg_wait<1>();
            release(n, 0, 1);
            if (j == 14) break;
            wg_wait<0>();
            TR(wg, ph * 64 + 16 + j * 2 + 1);
            release(n, 1, 1);
            releaseB(j & 1, 3);
            n = wrap(n + 4);
          }
          {
            const bool b0 = lane & 1, b1 = lane & 2, b2 = lane & 4;
            const float x0 = (b0 ? l[1] : l[0]) + __shfl_xor_sync(0xffffffffu, b0 ? l[0] : l[1], 1);
            const float x1 = (b0 ? l[3] : l[2]) + __shfl_xor_sync(0xffffffffu, b0 ? l[2] : l[3], 1);
            const float x2 = l[4] + __shfl_xor_sync(0xffffffffu, l[4], 1);
            const float y0 = (b1 ? x1 : x0) + __shfl_xor_sync(0xffffffffu, b1 ? x0 : x1, 2);
            const float y1 = x2 + __shfl_xor_sync(0xffffffffu, x2, 2);
            const float v = (b2 ? y1 : y0) + __shfl_xor_sync(0xffffffffu, b2 ? y0 : y1, 4);
            const int r = 4 * (lane & 7) + (lane >> 3);
            if (r < 19) asm volatile("st.shared.f32 [%0], %1;" ::"r"(sb + OFF_L + ((w * 4 + warp) * 19 + r) * 4), "f"(v) : "memory");
            __syncwarp();
            mbar_arrive_if(lane == 0, sb + BAR_LTOT, 1);
          }
          n = wrap(n + 2);
          a = acquire(n, 0);
          mbar_wait(sb + BAR_TFULL + 8, 1);
          TR(wg, ph * 64 + 16 + 30);
          mma_chunk(dA, a + w * 64, bd + CH / 16, 1);
          wg_commit();
          wg_wait<1>();
          TR(wg, ph * 64 + 16 + 29);
          release(n, -1, 1);
          releaseB(0, 3);
          a = acquire(n, 1);
          mma_chunk(dB, a + w * 64, bd + CH / 16, 1);
          wg_commit();
          mbar_wait(sb + BAR_LREADY, hh & 1);
          asm volatile("ld.shared.u32 %0, [%1];" : "=r"(skip) : "r"(sb + OFF_FLAG) : "memory");
          skip = __shfl_sync(0xffffffffu, skip == hh + 1, 0);
          if (skip) { mbar_wait(sb + BAR_SLOW, nslow & 1); nslow++; }
          wg_wait<1>();
          fence_regs(dA);
          release(n, 0, 1);
          TR(wg, ph * 64 + 16 + 31);
          {
            float2 sc[19];
            store_tile_T_scaled(dA, sb + OFF_Q + w * CH + st_off, linv, sc, !skip);
            wg_wait<0>();
            fence_regs(dB);
            release(n, 1, 1);
            releaseB(1, 3);
#pragma unroll
            for (int g = 0; g < 19; g++) { dB[4 * g] *= sc[g].x; dB[4 * g + 1] *= sc[g].y; dB[4 * g + 2] *= sc[g].x; dB[4 * g + 3] *= sc[g].y; }
            fence_regs(dB);
          }
          TR(wg, ph * 64 + 16 + 32);
          n = wrap(n + 2);
        } else {
          const uint32_t rnd = ph & 1, stage = sb + OFF_B + w * CH + st_off;
          mbar_wait(sb + BAR_PUB + 32, 1);
          uint32_t a = acquire(n, 0);
          TR(wg, ph * 64 + 12);
          mma_chunk(dB, a + w * 64, bd + 4 * (CH / 16), 1);
          wg_commit();
          wg_wait<1>();
          release(n, -1, 1);
          releaseB(1, 3);
          mbar_wait(sb + BAR_PUB + 40, 1);
          a = acquire(n, 1);
          mma_chunk(dB, a + w * 64, bd + 5 * (CH / 16), 1);
          wg_commit();
          wg_wait<1>();
          release(n, 0, 1);
          a = acquire(n, 2);
          TR(wg, ph * 64 + 14);
          mma_chunk(dA, a + w * 64, bd + 4 * (CH / 16), 1);
          wg_commit();
          mbar_wait(sb + BAR_BEMPTY + 8 * w, 1);
          a = acquire(n, 3);
          wg_wait<1>();
          fence_regs(dB);
          release(n, 1, 1);
          store_tile_T<0, 4, false>(dB, stage, 1.f);
          mma_chunk(dA, a + w * 64, bd + 5 * (CH / 16), 1);
          wg_commit();
          mbar_arrive_if(sig, sb + BAR_P2GO, 1);
          store_tile_T<4, 10, false>(dB, stage, 1.f);
          n = wrap(n + 4);
          a = acquire(n, 0);
          TR(wg, ph * 64 + 16);
          mma_chunk(dB, a + w * 64, bd + 3 * (CH / 16), 0);
          wg_commit();
          publish(sb + BAR_SG + 8 * w);
          wg_wait<1>();
          release(n, -2, 1);
          release(n, -1, 1);
          n = wrap(n + 2);
          auto pass2 = [&](uint32_t i0, uint32_t i1) {
#pragma unroll 1
            for (uint32_t i = i0; i < i1; i++) {
              const uint32_t u = 2 + ((i + 1) & 3);
              if (i >= 4) mbar_wait(sb + BAR_TFULL + 8 * u, rnd);
              const uint32_t a2 = acquire(n, 0);
              TR(wg, ph * 64 + 16 + i * 2);
              mma_chunk(dB, a2 + w * 64, bd + u * (CH / 16), 1);
              wg_commit();
              wg_wait<1>();
              release(n, -2, 1);
              releaseB(2 + (i & 3), 2);
              TR(wg, ph * 64 + 16 + i * 2 + 1);
              n = wrap(n + 2);
            }
          };
          pass2(1, 3 + 2 * w);
          fence_regs(dA);
          mbar_wait(sb + BAR_BEMPTY + 8 * w, 0);
          store_tile_T<0, 10, false>(dA, stage, 1.f);
          publish(sb + BAR_SG + 8 * w);
          pass2(3 + 2 * w, 8);
          if (ph == 5) break;
          skip = 0;
        }
      }
      mbar_wait(sb + BAR_BEMPTY + 8 * (3 + w), 1);
      wg_wait<0>();
      fence_regs(dB);
      store_tile_T<0, 10, false>(dB, sb + OFF_B + (3 + w) * CH + st_off, 1.f);
      publish(sb + BAR_SG + 8 * (3 + w));
      TR(wg, 400);
    }
  }
  __syncwarp();
  asm volatile("barrier.cluster.arrive.release.aligned;\nbarrier.cluster.wait.acquire.aligned;" ::: "memory");
}

typedef CUresult (*EncodeFn)(CUtensorMap*, CUtensorMapDataType, cuuint32_t, void*, const cuuint64_t*, const cuuint64_t*, const cuuint32_t*,
                             const cuuint32_t*, CUtensorMapInterleave, CUtensorMapSwizzle, CUtensorMapL2promotion, CUtensorMapFloatOOBfill);

void make_map4(EncodeFn fn, CUtensorMap* m, const void* ptr, uint64_t rows, uint64_t cols) {
  cuuint64_t dims[4] = {64, 8, cols / 64, rows / 8};
  cuuint64_t strides[3] = {cols * 2, 128, cols * 16};
  cuuint32_t box[4] = {64, 8, 2, 8}, es[4] = {1, 1, 1, 1};
  fn(m, CU_TENSOR_MAP_DATA_TYPE_BFLOAT16, 4, const_cast<void*>(ptr), dims, strides, box, es, CU_TENSOR_MAP_INTERLEAVE_NONE,
     CU_TENSOR_MAP_SWIZZLE_128B, CU_TENSOR_MAP_L2_PROMOTION_L2_128B, CU_TENSOR_MAP_FLOAT_OOB_FILL_NONE);
}
void make_map2(EncodeFn fn, CUtensorMap* m, const void* ptr, uint64_t rows, uint64_t cols, uint32_t box_rows) {
  cuuint64_t dims[2] = {cols, rows};
  cuuint64_t strides[1] = {cols * 2};
  cuuint32_t box[2] = {64, box_rows}, es[2] = {1, 1};
  fn(m, CU_TENSOR_MAP_DATA_TYPE_BFLOAT16, 2, const_cast<void*>(ptr), dims, strides, box, es, CU_TENSOR_MAP_INTERLEAVE_NONE,
     CU_TENSOR_MAP_SWIZZLE_128B, CU_TENSOR_MAP_L2_PROMOTION_L2_128B, CU_TENSOR_MAP_FLOAT_OOB_FILL_NONE);
}

}

extern "C" void kernel_launch(void* const* d_in, const int* in_sizes, int n_in, void* d_out, int out_size) {
  static EncodeFn fn = nullptr;
  if (!fn) {
    void* f = nullptr;
    cudaDriverEntryPointQueryResult st;
    cudaGetDriverEntryPoint("cuTensorMapEncodeTiled", &f, cudaEnableDefault, &st);
    fn = reinterpret_cast<EncodeFn>(f);
    cudaFuncSetAttribute(fused_mha_kernel, cudaFuncAttributeMaxDynamicSharedMemorySize, SMEM_BYTES);
  }
  Params p;
  for (int i = 0; i < 2; i++) {
    make_map2(fn, &p.x[i], d_in[5 * i + 0], NB * SQ, DM, NQ);
    make_map4(fn, &p.k[i], d_in[5 * i + 1], NB * NH * SK, DH);
    make_map4(fn, &p.v[i], d_in[5 * i + 2], NB * NH * SK, DH);
    make_map4(fn, &p.wq[i], d_in[5 * i + 3], DM, NH * DH);
    make_map4(fn, &p.wo[i], d_in[5 * i + 4], NH * DH, DM);
    p.kp[i] = (const __nv_bfloat16*)d_in[5 * i + 1];
    p.vp[i] = (const __nv_bfloat16*)d_in[5 * i + 2];
    p.wqp[i] = (const __nv_bfloat16*)d_in[5 * i + 3];
    p.wop[i] = (const __nv_bfloat16*)d_in[5 * i + 4];
  }
  make_map2(fn, &p.out[0], d_out, NB * SQ, 2 * DM, 40);
  make_map2(fn, &p.out[1], d_out, NB * SQ, 2 * DM, 32);
  p.outp = (__nv_bfloat16*)d_out;
  fused_mha_kernel<<<128, 512, SMEM_BYTES>>>(p);
}
```

```cpp
#include <cuda_runtime.h>
#include <cuda_bf16.h>
#include <cuda.h>
#include <stdint.h>

#define REG_S "120"
#define REG_O "184"
#define ST_PIECES 4
#define RED_PACED 11
#define ST2_A 3
#define ST2_B 5
#define F0 0
#define F1 1
#define WAIT_HINT ""
#define ST_POL pol_normal
#define ZROWS 38
#define EPI_SPLIT 3
#define SUM_MODE 1
#define Q_SPLIT 7
#define TURN_AT 7
#define NG 7

namespace {

constexpr int NB = 8, SQ = 304, DM = 448, NH = 16, SK = 1024, DH = 256;
constexpr int NQ = 152;
constexpr uint32_t GR = 16384;
constexpr uint32_t CH = NQ * 128;
constexpr uint32_t OFF_B = NG * GR;
constexpr uint32_t OFF_Q = OFF_B + 2 * CH;
constexpr uint32_t OFF_BAR = OFF_B + 6 * CH;
constexpr uint32_t BAR_FULL = OFF_BAR, BAR_EMPTY = OFF_BAR + 56;
constexpr uint32_t BAR_TFULL = OFF_BAR + 112;
constexpr uint32_t BAR_BEMPTY = OFF_BAR + 160;
constexpr uint32_t BAR_PUB = OFF_BAR + 208 - 16;
constexpr uint32_t BAR_SG = OFF_BAR + 240;
constexpr uint32_t BAR_PW = OFF_BAR + 288;
constexpr uint32_t BAR_LTOT = OFF_BAR + 304, BAR_LREADY = OFF_BAR + 312, BAR_STASH = OFF_BAR + 320, BAR_P2GO = OFF_BAR + 328;
constexpr uint32_t BAR_ST5 = OFF_BAR + 336, BAR_X4 = OFF_BAR + 344, BAR_SLOW = OFF_BAR + 352, BAR_Q0 = OFF_BAR + 360, BAR_X6 = OFF_BAR + 368;
constexpr uint32_t OFF_FLAG = OFF_BAR + 1016;
constexpr uint32_t OFF_L = OFF_BAR + 384;
constexpr uint32_t SMEM_USED = OFF_BAR + 1024;

struct Params {
  CUtensorMap x[2], k[2], v[2], wq[2], wo[2], wo6[2], out[2];
  const __nv_bfloat16* kp[2];
  const __nv_bfloat16* vp[2];
  __nv_bfloat16* outp;
};

__device__ uint4 g_stash[128 * 4 * (CH / 16)];
__device__ unsigned g_zero_cnt[32];

#define TRO(k)
#define TRO5(k)
#define TRO_DUMP(role)
#define TR(role, idx)
#define TR_DUMP(role)
constexpr uint32_t SMEM_BYTES = SMEM_USED;

template <int TA>
__device__ __forceinline__ void wgmma_n152(float (&d)[76], uint64_t da, uint64_t db, int scale_d) {
  asm volatile("{\n.reg .pred p;\nsetp.ne.b32 p, %78, 0;\n"
    "wgmma.mma_async.sync.aligned.m64n152k16.f32.bf16.bf16 "
    "{%0, %1, %2, %3, %4, %5, %6, %7, %8, %9, %10, %11, %12, %13, %14, %15, "
    "%16, %17, %18, %19, %20, %21, %22, %23, %24, %25, %26, %27, %28, %29, %30, %31, "
    "%32, %33, %34, %35, %36, %37, %38, %39, %40, %41, %42, %43, %44, %45, %46, %47, "
    "%48, %49, %50, %51, %52, %53, %54, %55, %56, %57, %58, %59, %60, %61, %62, %63, "
    "%64, %65, %66, %67, %68, %69, %70, %71, %72, %73, %74, %75}, "
    "%76, %77, p, 1, 1, %79, 0;\n}\n"
    : "+f"(d[0]), "+f"(d[1]), "+f"(d[2]), "+f"(d[3]), "+f"(d[4]), "+f"(d[5]), "+f"(d[6]), "+f"(d[7]),
      "+f"(d[8]), "+f"(d[9]), "+f"(d[10]), "+f"(d[11]), "+f"(d[12]), "+f"(d[13]), "+f"(d[14]), "+f"(d[15]),
      "+f"(d[16]), "+f"(d[17]), "+f"(d[18]), "+f"(d[19]), "+f"(d[20]), "+f"(d[21]), "+f"(d[22]), "+f"(d[23]),
      "+f"(d[24]), "+f"(d[25]), "+f"(d[26]), "+f"(d[27]), "+f"(d[28]), "+f"(d[29]), "+f"(d[30]), "+f"(d[31]),
      "+f"(d[32]), "+f"(d[33]), "+f"(d[34]), "+f"(d[35]), "+f"(d[36]), "+f"(d[37]), "+f"(d[38]), "+f"(d[39]),
      "+f"(d[40]), "+f"(d[41]), "+f"(d[42]), "+f"(d[43]), "+f"(d[44]), "+f"(d[45]), "+f"(d[46]), "+f"(d[47]),
      "+f"(d[48]), "+f"(d[49]), "+f"(d[50]), "+f"(d[51]), "+f"(d[52]), "+f"(d[53]), "+f"(d[54]), "+f"(d[55]),
      "+f"(d[56]), "+f"(d[57]), "+f"(d[58]), "+f"(d[59]), "+f"(d[60]), "+f"(d[61]), "+f"(d[62]), "+f"(d[63]),
      "+f"(d[64]), "+f"(d[65]), "+f"(d[66]), "+f"(d[67]), "+f"(d[68]), "+f"(d[69]), "+f"(d[70]), "+f"(d[71]),
      "+f"(d[72]), "+f"(d[73]), "+f"(d[74]), "+f"(d[75])
    : "l"(da), "l"(db), "r"(scale_d), "n"(TA));
}

__device__ __forceinline__ void wg_fence() { asm volatile("wgmma.fence.sync.aligned;" ::: "memory"); }
__device__ __forceinline__ void wg_commit() { asm volatile("wgmma.commit_group.sync.aligned;" ::: "memory"); }
template <int N> __device__ __forceinline__ void wg_wait() { asm volatile("wgmma.wait_group.sync.aligned %0;" ::"n"(N) : "memory"); }
template <int N> __device__ __forceinline__ void fence_regs(float (&d)[N]) {
#pragma unroll
  for (int i = 0; i < N; i++) asm volatile("" : "+f"(d[i])::"memory");
}
template <uint32_t SBO> __device__ __forceinline__ uint64_t desc(uint32_t a16) {
  return (uint64_t)a16 | ((uint64_t)((SBO >> 4) | 0x40000000u) << 32);
}
__device__ __forceinline__ void mbar_init(uint32_t bar, uint32_t cnt) { asm volatile("mbarrier.init.shared::cta.b64 [%0], %1;" ::"r"(bar), "r"(cnt) : "memory"); }
__device__ __forceinline__ void mbar_expect(uint32_t bar, uint32_t bytes) { asm volatile("mbarrier.arrive.expect_tx.shared::cta.b64 _, [%0], %1;" ::"r"(bar), "r"(bytes) : "memory"); }
__device__ __forceinline__ void mbar_arrive(uint32_t bar, uint32_t cnt) { asm volatile("mbarrier.arrive.shared::cta.b64 _, [%0], %1;" ::"r"(bar), "r"(cnt) : "memory"); }
__device__ __forceinline__ void mbar_arrive_cluster(uint32_t bar, uint32_t cnt) { asm volatile("mbarrier.arrive.shared::cluster.b64 _, [%0], %1;" ::"r"(bar), "r"(cnt) : "memory"); }
__device__ __forceinline__ void mbar_arrive_if(bool c, uint32_t bar, uint32_t cnt) {
  asm volatile("{\n.reg .pred p;\nsetp.ne.u32 p, %2, 0;\n@p mbarrier.arrive.shared::cta.b64 _, [%0], %1;\n}" ::"r"(bar), "r"(cnt), "r"((uint32_t)c) : "memory");
}
__device__ __forceinline__ void mbar_arrive_cluster_if(bool c, uint32_t bar, uint32_t cnt) {
  asm volatile("{\n.reg .pred p;\nsetp.ne.u32 p, %2, 0;\n@p mbarrier.arrive.shared::cluster.b64 _, [%0], %1;\n}" ::"r"(bar), "r"(cnt), "r"((uint32_t)c) : "memory");
}
__device__ __forceinline__ uint32_t mbar_test(uint32_t bar, uint32_t parity) {
  uint32_t ok;
  asm volatile("{\n.reg .pred p;\nmbarrier.test_wait.parity.shared::cta.b64 p, [%1], %2;\nselp.u32 %0, 1, 0, p;\n}" : "=r"(ok) : "r"(bar), "r"(parity) : "memory");
  return ok;
}
__device__ __forceinline__ void mbar_wait(uint32_t bar, uint32_t parity) {
  asm volatile(
      "{\n.reg .pred p;\n.reg .u32 n;\n"
      "mbarrier.try_wait.parity.shared::cta.b64 p, [%0], %1;\n"
      "@p bra.uni DONE;\n"
      "mov.u32 n, 0;\n"
      "LOOP:\n"
      "mbarrier.try_wait.parity.shared::cta.b64 p, [%0], %1" WAIT_HINT ";\n"
      "@p bra.uni DONE;\n"
      "add.u32 n, n, 1;\n"
      "setp.lt.u32 p, n, 0x4000000;\n"
      "@p bra.uni LOOP;\n"
      "trap;\n"
      "DONE:\n}" ::"r"(bar), "r"(parity) : "memory");
}
__device__ __forceinline__ void mbar_wait_unless(uint32_t ok, uint32_t bar, uint32_t parity) {
  asm volatile(
      "{\n.reg .pred p;\n.reg .u32 n;\n"
      "setp.ne.u32 p, %2, 0;\n"
      "@p bra.uni DONE;\n"
      "mov.u32 n, 0;\n"
      "LOOP:\n"
      "mbarrier.try_wait.parity.shared::cta.b64 p, [%0], %1;\n"
      "@p bra.uni DONE;\n"
      "add.u32 n, n, 1;\n"
      "setp.lt.u32 p, n, 0x4000000;\n"
      "@p bra.uni LOOP;\n"
      "trap;\n"
      "DONE:\n}" ::"r"(bar), "r"(parity), "r"(ok) : "memory");
}
__device__ __forceinline__ void mbar_wait2(uint32_t bar0, uint32_t par0, uint32_t bar1, uint32_t par1) {
  const uint32_t ok = mbar_test(bar1, par1);
  mbar_wait(bar0, par0);
  mbar_wait_unless(ok, bar1, par1);
}
__device__ __forceinline__ void fence_async_smem() { asm volatile("fence.proxy.async.shared::cta;" ::: "memory"); }
__device__ __forceinline__ void cluster_arrive() { __syncwarp(); asm volatile("barrier.cluster.arrive.relaxed.aligned;" ::: "memory"); }
__device__ __forceinline__ void bar_arrive(int id, int n) { asm volatile("bar.arrive %0, %1;" ::"r"(id), "r"(n) : "memory"); }
__device__ __forceinline__ void bar_sync(int id, int n) { asm volatile("bar.sync %0, %1;" ::"r"(id), "r"(n) : "memory"); }
#define ELECT "{\n.reg .pred e;\nelect.sync _|e, 0xffffffff;\n"
__device__ __forceinline__ void tma4_mc(uint32_t dst, const CUtensorMap* m, int c2, int c3, uint32_t bar, uint32_t bar_peer, uint64_t pol) {
  asm volatile(ELECT
               "@e cp.async.bulk.tensor.4d.shared::cluster.global.mbarrier::complete_tx::bytes.multicast::cluster.L2::cache_hint [%0], [%1, {%2, %2, %3, %4}], [%5], %6, %7;\n"
               "@e mbarrier.arrive.expect_tx.shared::cta.b64 _, [%5], 16384;\n"
               "@e mbarrier.arrive.expect_tx.shared::cluster.b64 _, [%8], 16384;\n}"
               ::"r"(dst), "l"(m), "r"(0), "r"(c2), "r"(c3), "r"(bar), "h"((uint16_t)3), "l"(pol), "r"(bar_peer) : "memory");
}
__device__ __forceinline__ void tma2(uint32_t dst, const CUtensorMap* m, int c0, int c1, uint32_t bar) {
  asm volatile(ELECT
               "@e cp.async.bulk.tensor.2d.shared::cluster.global.mbarrier::complete_tx::bytes [%0], [%1, {%2, %3}], [%4];\n"
               "@e mbarrier.arrive.expect_tx.shared::cta.b64 _, [%4], 19456;\n"
               "@e mbarrier.arrive.shared::cta.b64 _, [%4], 3;\n}"
               ::"r"(dst), "l"(m), "r"(c0), "r"(c1), "r"(bar) : "memory");
}
__device__ __forceinline__ void bulk_g2s(uint32_t dst, const void* src, uint32_t bar, uint64_t pol) {
  asm volatile(ELECT
               "@e cp.async.bulk.shared::cluster.global.mbarrier::complete_tx::bytes.L2::cache_hint [%0], [%1], 19456, [%2], %3;\n"
               "@e mbarrier.arrive.expect_tx.shared::cta.b64 _, [%2], 19456;\n"
               "@e mbarrier.arrive.shared::cta.b64 _, [%2], 3;\n}"
               ::"r"(dst), "l"(src), "r"(bar), "l"(pol) : "memory");
}
__device__ __forceinline__ void bulk_s2g(void* dst, uint32_t src, uint32_t bytes, uint64_t pol) {
  asm volatile(ELECT "@e cp.async.bulk.global.shared::cta.bulk_group.L2::cache_hint [%0], [%1], %2, %3;\n}" ::"l"(dst), "r"(src), "r"(bytes), "l"(pol) : "memory");
}
__device__ __forceinline__ void tma_red2(const CUtensorMap* m, int c0, int c1, uint32_t src) {
  asm volatile(ELECT "@e cp.reduce.async.bulk.tensor.2d.global.shared::cta.add.tile.bulk_group [%0, {%1, %2}], [%3];\n}" ::"l"(m), "r"(c0), "r"(c1), "r"(src) : "memory");
}
__device__ __forceinline__ void mbar_arrive_one(uint32_t bar, uint32_t cnt) {
  asm volatile(ELECT "@e mbarrier.arrive.shared::cta.b64 _, [%0], %1;\n}" ::"r"(bar), "r"(cnt) : "memory");
}
__device__ __forceinline__ void bulk_commit_wait_read() { asm volatile("cp.async.bulk.commit_group;\ncp.async.bulk.wait_group.read 0;" ::: "memory"); }
__device__ __forceinline__ uint32_t pack_bf16(float lo, float hi) {
  uint32_t r;
  asm("cvt.rn.bf16x2.f32 %0, %1, %2;" : "=r"(r) : "f"(hi), "f"(lo));
  return r;
}
__device__ __forceinline__ void stsm4t(uint32_t a, uint32_t r0, uint32_t r1, uint32_t r2, uint32_t r3) {
  asm volatile("stmatrix.sync.aligned.m8n8.x4.trans.shared.b16 [%0], {%1, %2, %3, %4};" ::"r"(a), "r"(r0), "r"(r1), "r"(r2), "r"(r3) : "memory");
}
__device__ __forceinline__ void stsm2t(uint32_t a, uint32_t r0, uint32_t r1) {
  asm volatile("stmatrix.sync.aligned.m8n8.x2.trans.shared.b16 [%0], {%1, %2};" ::"r"(a), "r"(r0), "r"(r1) : "memory");
}
__device__ __forceinline__ float ex2(float x) { float y; asm("ex2.approx.ftz.f32 %0, %1;" : "=f"(y) : "f"(x)); return y; }
__device__ __forceinline__ float2 lds64f(uint32_t a) { float2 v; asm volatile("ld.shared.v2.f32 {%0, %1}, [%2];" : "=f"(v.x), "=f"(v.y) : "r"(a) : "memory"); return v; }

template <int G0, int G1, bool SCALE>
__device__ __forceinline__ void store_tile_T(const float (&d)[76], uint32_t a, float c) {
#pragma unroll
  for (int g = G0; g < G1; g++) {
    float v[8];
#pragma unroll
    for (int i = 0; i < 8; i++) v[i] = 8 * g + i < 76 ? (SCALE ? d[8 * g + i] * c : d[8 * g + i]) : 0.f;
    if (g < 9) stsm4t(a + g * 2048, pack_bf16(v[0], v[1]), pack_bf16(v[2], v[3]), pack_bf16(v[4], v[5]), pack_bf16(v[6], v[7]));
    else stsm2t(a + g * 2048, pack_bf16(v[0], v[1]), pack_bf16(v[2], v[3]));
  }
}
__device__ __forceinline__ void stsm4t_if(bool on, uint32_t a, uint32_t r0, uint32_t r1, uint32_t r2, uint32_t r3) {
  asm volatile("{\n.reg .pred p;\nsetp.ne.u32 p, %5, 0;\n@p stmatrix.sync.aligned.m8n8.x4.trans.shared.b16 [%0], {%1, %2, %3, %4};\n}"
               ::"r"(a), "r"(r0), "r"(r1), "r"(r2), "r"(r3), "r"((uint32_t)on) : "memory");
}
__device__ __forceinline__ void stsm2t_if(bool on, uint32_t a, uint32_t r0, uint32_t r1) {
  asm volatile("{\n.reg .pred p;\nsetp.ne.u32 p, %3, 0;\n@p stmatrix.sync.aligned.m8n8.x2.trans.shared.b16 [%0], {%1, %2};\n}"
               ::"r"(a), "r"(r0), "r"(r1), "r"((uint32_t)on) : "memory");
}
__device__ __forceinline__ float rcp(float x) { float y; asm("rcp.approx.ftz.f32 %0, %1;" : "=f"(y) : "f"(x)); return y; }
__device__ __forceinline__ uint4 lds128(uint32_t a) {
  uint4 v;
  asm volatile("ld.shared.v4.u32 {%0, %1, %2, %3}, [%4];" : "=r"(v.x), "=r"(v.y), "=r"(v.z), "=r"(v.w) : "r"(a) : "memory");
  return v;
}
__device__ __forceinline__ uint32_t hadd2(uint32_t a, uint32_t b) { uint32_t r; asm("add.rn.bf16x2 %0, %1, %2;" : "=r"(r) : "r"(a), "r"(b)); return r; }
__device__ __forceinline__ float sum8(uint4 v) {
  const uint32_t a = hadd2(v.x, v.y), b = hadd2(v.z, v.w);
  return (__uint_as_float(a << 16) + __uint_as_float(a & 0xffff0000u)) + (__uint_as_float(b << 16) + __uint_as_float(b & 0xffff0000u));
}
__device__ __forceinline__ void mma_chunk(float (&d)[76], uint32_t a, uint32_t b, int acc) {
  wg_fence();
#pragma unroll
  for (int ks = 0; ks < 4; ks++) wgmma_n152<1>(d, desc<2048>(a + ks * 256), desc<1024>(b + ks * 2), ks == 0 ? acc : 1);
}

__device__ __forceinline__ void qk_steps(float (&s)[76], uint32_t a, uint32_t q, bool first, int k0, int k1) {
  q += a >> 20;
  wg_fence();
#pragma unroll
  for (int ks = k0; ks < k1; ks++)
    wgmma_n152<0>(s, desc<2048>(a + (ks >> 2) * 64 + (ks & 3) * 2), desc<1024>(q + (ks >> 2) * (CH / 16) + (ks & 3) * 2), !(first && ks == 0));
}
__device__ __forceinline__ void exp_store(const float (&s)[76], uint32_t pa, int g0, int g1) {
#pragma unroll
  for (int g = g0; g < g1 && g < 9; g++)
    stsm4t(pa + g * 2048, pack_bf16(ex2(s[8 * g]), ex2(s[8 * g + 1])), pack_bf16(ex2(s[8 * g + 2]), ex2(s[8 * g + 3])),
           pack_bf16(ex2(s[8 * g + 4]), ex2(s[8 * g + 5])), pack_bf16(ex2(s[8 * g + 6]), ex2(s[8 * g + 7])));
  if (g1 == 10) stsm2t(pa + 9 * 2048, pack_bf16(ex2(s[72]), ex2(s[73])), pack_bf16(ex2(s[74]), ex2(s[75])));
}

constexpr float SCALE_LOG2E = 0.0625f * 1.4426950408889634f;

__device__ __forceinline__ void slow_path(uint32_t qbuf, const __nv_bfloat16* kp, const __nv_bfloat16* vp, int warp, int lane) {
#pragma unroll 1
  for (int r = warp; r < NQ; r += 4) {
    uint32_t a = qbuf + (lane >> 3) * CH + r * 128 + (((lane & 7) ^ (r & 7)) << 4);
    uint32_t qv[4];
    asm volatile("ld.shared.v4.u32 {%0, %1, %2, %3}, [%4];" : "=r"(qv[0]), "=r"(qv[1]), "=r"(qv[2]), "=r"(qv[3]) : "r"(a) : "memory");
    float q[8], o[8];
#pragma unroll
    for (int i = 0; i < 4; i++) { q[2 * i] = __uint_as_float(qv[i] << 16); q[2 * i + 1] = __uint_as_float(qv[i] & 0xffff0000u); }
#pragma unroll
    for (int i = 0; i < 8; i++) o[i] = 0.f;
    float m = -INFINITY, l = 0.f;
#pragma unroll 2
    for (int t = 0; t < SK; t++) {
      uint4 kv = __ldg(reinterpret_cast<const uint4*>(kp + (size_t)t * DH) + lane);
      uint4 vv = __ldg(reinterpret_cast<const uint4*>(vp + (size_t)t * DH) + lane);
      uint32_t kw[4] = {kv.x, kv.y, kv.z, kv.w}, vw[4] = {vv.x, vv.y, vv.z, vv.w};
      float s = 0.f;
#pragma unroll
      for (int i = 0; i < 4; i++) s = fmaf(q[2 * i], __uint_as_float(kw[i] << 16), fmaf(q[2 * i + 1], __uint_as_float(kw[i] & 0xffff0000u), s));
#pragma unroll
      for (int x = 16; x > 0; x >>= 1) s += __shfl_xor_sync(0xffffffffu, s, x);
      float mn = fmaxf(m, s);
      float corr = (m == mn) ? 1.f : exp2f(m - mn), p = exp2f(s - mn);
      m = mn;
      l = l * corr + p;
#pragma unroll
      for (int i = 0; i < 4; i++) {
        o[2 * i] = fmaf(p, __uint_as_float(vw[i] << 16), o[2 * i] * corr);
        o[2 * i + 1] = fmaf(p, __uint_as_float(vw[i] & 0xffff0000u), o[2 * i + 1] * corr);
      }
    }
    float inv = 1.f / l;
    asm volatile("st.shared.v4.u32 [%0], {%1, %2, %3, %4};" ::"r"(a), "r"(pack_bf16(o[0] * inv, o[1] * inv)), "r"(pack_bf16(o[2] * inv, o[3] * inv)),
                 "r"(pack_bf16(o[4] * inv, o[5] * inv)), "r"(pack_bf16(o[6] * inv, o[7] * inv)) : "memory");
  }
}

__global__ void __cluster_dims__(2, 1, 1) __launch_bounds__(512, 1) fused_mha_kernel(const __grid_constant__ Params p) {
  extern __shared__ __align__(1024) uint8_t smem_raw[];
  const uint32_t sb = __shfl_sync(0xffffffffu, (uint32_t)__cvta_generic_to_shared(smem_raw), 0);
  const int wg = __shfl_sync(0xffffffffu, (int)(threadIdx.x >> 7), 0);
  const int warp = __shfl_sync(0xffffffffu, (int)((threadIdx.x >> 5) & 3), 0);
  const int lane = __shfl_sync(0xffffffffu, (int)(threadIdx.x & 31), threadIdx.x & 31);
  if (wg == 0 && warp == 0) {
    const int cta = blockIdx.x, br = cta >> 6;
    asm volatile(ELECT
                 "@e mbarrier.init.shared::cta.b64 [%0], 1;\n@e mbarrier.init.shared::cta.b64 [%0 + 8], 1;\n@e mbarrier.init.shared::cta.b64 [%0 + 112], 4;\n"
                 "fence.proxy.async.shared::cta;\n"
                 "@e cp.async.bulk.tensor.4d.shared::cluster.global.mbarrier::complete_tx::bytes [%1], [%2, {%3, %3, %4, %3}], [%0];\n"
                 "@e cp.async.bulk.tensor.4d.shared::cluster.global.mbarrier::complete_tx::bytes [%1 + 16384], [%2, {%3, %3, %5, %3}], [%0 + 8];\n"
                 "@e mbarrier.arrive.expect_tx.shared::cta.b64 _, [%0], 16384;\n@e mbarrier.arrive.expect_tx.shared::cta.b64 _, [%0 + 8], 16384;\n}"
                 ::"r"(sb + OFF_BAR), "r"(sb), "l"(&p.wq[br]), "r"(0), "r"(((cta >> 1) & 3) * 16), "r"(((cta >> 1) & 3) * 16 + 2) : "memory");
    tma2(sb + OFF_B, &p.x[br], 0, ((cta >> 3) & 7) * SQ + (cta & 1) * NQ, sb + BAR_TFULL);
    if (sb & 1023) asm volatile("trap;");
    TR(0, 0);
  }
  {
    const uint32_t v = wg * 4 + warp;
    asm volatile(ELECT ".reg .pred q;\nsetp.ne.and.u32 q, %4, 0, e;\n"
                 "@q mbarrier.init.shared::cta.b64 [%0], %1;\n@e mbarrier.init.shared::cta.b64 [%0 + 128], %2;\n@e mbarrier.init.shared::cta.b64 [%0 + 256], %3;\n}"
                 ::"r"(sb + OFF_BAR + 8 * v), "r"(v < 7 ? 1 : 4), "r"(v >= 4 && v < 10 ? 6 : 4), "r"((uint32_t)(0x1114212112444444ull >> (4 * v)) & 15),
                   "r"((uint32_t)(v > 1 && v != 14)) : "memory");
    asm volatile("fence.mbarrier_init.release.cluster;" ::: "memory");
  }
  TR(0, 30);
  asm volatile("barrier.cluster.arrive.relaxed.aligned;\nbarrier.cluster.wait.aligned;" ::: "memory");
  TR(0, 24);

  if (wg == 0) {
    asm volatile("setmaxnreg.dec.sync.aligned.u32 24;");
    int cta;
    asm volatile("mov.u32 %0, %%ctaid.x;" : "=r"(cta));
    const int rank = cta & 1, br = cta >> 6, b = (cta >> 3) & 7, hg = (cta >> 1) & 3;
    const int xrow = b * SQ + rank * NQ;
    char* stash = reinterpret_cast<char*>(g_stash) + (size_t)cta * (4 * CH);
    uint64_t pol_first, pol_normal;
    asm volatile("createpolicy.fractional.L2::evict_first.b64 %0, 1.0;" : "=l"(pol_first));
    asm volatile("createpolicy.fractional.L2::evict_normal.b64 %0, 1.0;" : "=l"(pol_normal));
    auto load_x = [&](uint32_t u, int c) { tma2(sb + OFF_B + u * CH, &p.x[br], c * 64, xrow, sb + BAR_TFULL + 8 * u); };
    if (warp == 0) {
      uint32_t full_peer;
      asm volatile("mapa.shared::cluster.u32 %0, %1, %2;" : "=r"(full_peer) : "r"(sb + BAR_FULL), "r"(rank ^ 1));
      int m = rank + 2, rnd = 0;
      uint32_t slot = rank + 2, k = 0;
#pragma unroll 1
      for (int n = rank + 2; n < 368; n += 2) {
        const CUtensorMap* map;
        int c2, c3;
        uint64_t pol = pol_normal;
        if (m < 156) {
          const int hb = m >= 78, g = m - hb * 78, h = hg * 4 + rnd * 2 + hb;
          if (g < 14) {
            map = &p.wq[br];
            c2 = h * 4 + (g < 10 ? g & 1 : (g - 10) >> 1) * 2;
            c3 = (g < 10 ? g >> 1 : 5 + (g & 1)) * 8;
          } else {
            int it = (g - 14) >> 1;
            if (it == 2 || it == 3) it ^= 1;
            const bool isv = it == 31 || (it > 0 && !(it & 1));
            map = isv ? &p.v[br] : &p.k[br];
            c2 = (g & 1) * 2;
            c3 = (b * NH + h) * (SK / 8) + (isv ? (it - 1) >> 1 : (it + 1) >> 1) * 8;
            pol = pol_first;
          }
        } else {
          const int g = m - 156;
          int kc;
          if (g < 16) {
            const int c = g < 12 ? g >> 1 : 6 + (g & 1);
            kc = (0x76325410 >> (c * 4)) & 7;
            c2 = (g < 12 ? g & 1 : g < 14) * 2;
            map = &p.wo[br];
          } else {
            const int pr = (g - 16) / 3, e = g - 16 - pr * 3;
            kc = ((0x2046 >> (pr * 4)) & 7) + (e == 2);
            c2 = e == 1 ? 6 : 4;
            map = e == 1 ? &p.wo6[br] : &p.wo[br];
          }
          c3 = (hg * 4 + rnd * 2) * 32 + kc * 8;
        }
        if (k > 0) mbar_wait(sb + BAR_EMPTY + 8 * slot, (NG & 1) ? ((k - 1) >> 1) & 1 : (k - 1) & 1);
        tma4_mc(sb + slot * GR, map, c2, c3, sb + BAR_FULL + 8 * slot, full_peer + 8 * slot, pol);
        if (n < 40) TR(0, n >> 1);
        slot += 2;
        if (slot >= NG) { slot -= NG; k++; }
        m += 2;
        if (m >= 184) { m -= 184; rnd++; }
      }
    } else if (warp == 1) {
      mbar_wait(sb + BAR_TFULL, 0);
      load_x(2, 2);
      mbar_wait(sb + BAR_TFULL + 16, 0);
      load_x(3, 4);
      mbar_wait(sb + BAR_TFULL + 24, 0);
      load_x(5, 6);
#pragma unroll 1
      for (int rnd = 0; rnd < 2; rnd++) {
        mbar_wait(sb + BAR_LREADY, 0);
#pragma unroll 1
        for (uint32_t i = 0; i < 4; i++) {
          const uint32_t u = (0x4532 >> (4 * i)) & 7;
          mbar_wait(sb + BAR_PUB + 8 * u, 1);
#pragma unroll 1
          for (uint32_t o = 0; o < CH; o += CH / ST_PIECES) {
            bulk_s2g(stash + (u - 2) * CH + o, sb + OFF_B + u * CH + o, CH / ST_PIECES, ST_POL);
            bulk_commit_wait_read();
          }
          if (i < 3) load_x(u, 2 * i + 2);
        }
        mbar_arrive_one(sb + BAR_ST5, 1);
        asm volatile("cp.async.bulk.wait_group 0;\nfence.proxy.async;" ::: "memory");
        mbar_arrive_one(sb + BAR_STASH, 1);
        mbar_wait(sb + BAR_LREADY, 1);
#pragma unroll 1
        for (uint32_t i = 0; i < 4; i++) {
          const uint32_t u = 2 + (i ^ 2);
          mbar_wait(sb + BAR_BEMPTY + 8 * u, 0);
          bulk_g2s(sb + OFF_B + u * CH, stash + i * CH, sb + BAR_TFULL + 8 * u, pol_normal);
          TR(0, 32 + rnd * 4 + i);
        }
        if (rnd == 0) { mbar_wait(sb + BAR_BEMPTY + 24, 1); load_x(3, 2); }
      }
    } else if (warp == 2) {
#pragma unroll 1
      for (int ph = 0; ph < 6; ph++) {
        const bool isP = ph == 2 || ph == 5;
        if (ph == 3) {
          mbar_wait(sb + BAR_BEMPTY, 1); mbar_wait(sb + BAR_BEMPTY + 8, 1);
          mbar_wait(sb + BAR_BEMPTY + 8 * F0, 0); mbar_wait(sb + BAR_BEMPTY + 8 * (1 - F0), 0);
        } else if (ph > 0) {
          mbar_wait(sb + BAR_LTOT, isP);
        }
        if (isP) { mbar_wait(sb + BAR_STASH, ph & 1); asm volatile("fence.proxy.async;" ::: "memory"); }
#pragma unroll 1
        for (uint32_t i = ph == 0; i < 4; i++) {
          const uint32_t u = i & 1;
          mbar_wait(sb + BAR_BEMPTY + 8 * u, i < 2);
          if (isP) bulk_g2s(sb + OFF_B + u * CH, stash + i * CH, sb + BAR_TFULL + 8 * u, pol_normal);
          else load_x(u, (0x5310 >> (4 * i)) & 7);
        }
      }
    } else {
      asm volatile(ELECT "@e prefetch.tensormap [%0];\n@e prefetch.tensormap [%1];\n}" ::"l"(&p.k[br]), "l"(&p.v[br]) : "memory");
      mbar_wait(sb + BAR_PUB + 40, 0);
      {
        char* o = reinterpret_cast<char*>(p.outp) + (size_t)(xrow + hg * 38) * (2 * DM * 2) + br * (DM * 2) + lane * 16;
#pragma unroll 1
        for (int i = 0; i < ZROWS; i++) {
          *reinterpret_cast<uint4*>(o) = make_uint4(0, 0, 0, 0);
          if (lane < 24) *reinterpret_cast<uint4*>(o + 512) = make_uint4(0, 0, 0, 0);
          o += 2 * DM * 2;
          __nanosleep(200);
        }
      }
      asm volatile("fence.proxy.async;" ::: "memory");
      __threadfence();
      __syncwarp();
      unsigned* cnt = &g_zero_cnt[(cta >> 3) * 2 + rank];
      unsigned target = 0;
      if (lane == 0) target = (atomicAdd(cnt, 1) & ~3u) + 4;
      target = __shfl_sync(0xffffffffu, target, 0);
      mbar_wait(sb + BAR_STASH, 0);
#pragma unroll 1
      for (unsigned n = 0;; n++) {
        unsigned v;
        asm volatile("ld.acquire.gpu.global.u32 %0, [%1];" : "=r"(v) : "l"(cnt) : "memory");
        if ((int)(v - target) >= 0) break;
        if (n > (1u << 24)) asm volatile("trap;");
      }
      asm volatile("fence.proxy.async;" ::: "memory");
      __syncwarp();
      auto drained = [&](int i) {
        const int q = i > 7 ? i - 8 : i - 1;
        if (q < 4) mbar_arrive_one(sb + BAR_BEMPTY + 8 * ((q ^ (i > 7 ? F1 : F0)) & 1), 6);
        else if (q == 6) mbar_arrive_one(sb + BAR_ST5, 1);
        else load_x(q == 4 ? 2 : 5, q == 4 ? 4 : 6);
      };
#pragma unroll 1
      for (int i = 0; i < 14; i++) {
        const int rnd = i >= 7, q = i - rnd * 7;
        const uint32_t u = ((rnd ? (F1 ? 0x4010101 : 0x5101010) : (F0 ? 0x4520101 : 0x4521010)) >> (4 * q)) & 7, par = u < 2 ? (q >> 1) & 1 : rnd;
        const int t = ((rnd ? (F1 ? 0x4560123 : 0x5461032) : (F0 ? 0x4560123 : 0x4561032)) >> (4 * q)) & 7;
        bool pending = i > 0 && i < 12;
        if (pending && !__any_sync(0xffffffffu, mbar_test(sb + BAR_SG + 8 * u, par))) {
          asm volatile("cp.async.bulk.wait_group.read 0;" ::: "memory");
          drained(i);
          pending = false;
        }
        mbar_wait(sb + BAR_SG + 8 * u, par);
        TR(0, 98 + i);
#pragma unroll 1
        for (int g = 0; g < 4; g++) {
          tma_red2(&p.out[g == 3], br * DM + t * 64, xrow + g * 40, sb + OFF_B + u * CH + g * 5120);
          asm volatile("cp.async.bulk.commit_group;" ::: "memory");
          if (i < RED_PACED || (g == 0 && pending)) asm volatile("cp.async.bulk.wait_group.read 1;" ::: "memory");
          if (g == 0 && pending) drained(i);
        }
      }
      asm volatile("cp.async.bulk.wait_group.read 0;" ::: "memory");
      TR(0, 96);
    }
    TR_DUMP(0);
  } else {
    uint32_t empty0, empty1;
    asm volatile("mapa.shared::cluster.u32 %0, %1, 0;" : "=r"(empty0) : "r"(sb + BAR_EMPTY));
    asm volatile("mapa.shared::cluster.u32 %0, %1, 1;" : "=r"(empty1) : "r"(sb + BAR_EMPTY));
    const bool sig = warp == 0 && lane == 0;
    const uint32_t sd = (sb & 0x3FFFF) >> 4;
    const uint32_t st_off = (lane >> 4) * 1024 + (lane & 7) * 128 + (((2 * warp + ((lane >> 3) & 1)) ^ (lane & 7)) << 4);
    auto wrap = [](uint32_t q) { return q >= 2 * NG ? q - 2 * NG : q; };
    auto acquire = [&](uint32_t n, int k) {
      const uint32_t q = wrap(n + k), slot = q >= NG ? q - NG : q;
      mbar_wait(sb + BAR_FULL + 8 * slot, q >= NG);
      return sd + slot * (GR / 16);
    };
    auto gbar = [&](uint32_t n, int k) {
      const uint32_t q = wrap(n + k);
      return sb + BAR_FULL + 8 * (q >= NG ? q - NG : q);
    };
    auto gpar = [&](uint32_t n, int k) { return (uint32_t)(wrap(n + k) >= NG); };
    auto gaddr = [&](uint32_t n, int k) {
      const uint32_t q = wrap(n + k);
      return sd + (q >= NG ? q - NG : q) * (GR / 16);
    };
    auto release = [&](uint32_t n, int k, uint32_t cnt) {
      const uint32_t q = wrap(n + (k < 0 ? k + 2 * NG : k)), slot = q >= NG ? q - NG : q;
      mbar_arrive_cluster_if(sig, (((q + NG) & 1) ? empty1 : empty0) + 8 * slot, cnt);
    };
    auto releaseB = [&](uint32_t u, uint32_t cnt) { mbar_arrive_if(sig, sb + BAR_BEMPTY + 8 * u, cnt); };
    auto publish = [&](uint32_t bar) {
      fence_async_smem();
      __syncwarp();
      mbar_arrive_if(lane == 0, bar, 1);
    };
    const uint32_t bd = sd + OFF_B / 16;
    if (wg == 1) {
      asm volatile("setmaxnreg.dec.sync.aligned.u32 " REG_S ";");
      float s[76];
#pragma unroll
      for (int i = 0; i < 76; i++) s[i] = 0.f;
      fence_regs(s);
      const uint32_t qd = bd + 2 * (CH / 16);
#pragma unroll 1
      for (int hh = 0; hh < 4; hh++) {
        uint32_t n = hh == 0 ? 14 % (2 * NG) : hh == 1 ? 92 % (2 * NG) : hh == 2 ? 198 % (2 * NG) : 276 % (2 * NG);
        uint32_t okp;
        {
          mbar_wait(sb + BAR_X4, hh & 1);
          uint32_t a = acquire(n, 0);
          mbar_wait2(sb + BAR_PUB + 16, 0, sb + BAR_PUB + 24, 0);
          TR(1, (hh * 16) * 4);
          qk_steps(s, a, qd, true, 0, 8);
          wg_commit();
          a = acquire(n, 1);
          mbar_wait(sb + BAR_PUB + 32, 0);
          qk_steps(s, a, qd + 2 * (CH / 16), false, 0, 4);
          mbar_wait(sb + BAR_PUB + 40, 0);
          qk_steps(s, a, qd + 2 * (CH / 16), false, 4, 8);
          wg_commit();
          mbar_arrive_if(sig, sb + BAR_Q0, 1);
          wg_wait<1>();
          release(n, 0, 2);
          okp = mbar_test(sb + BAR_BEMPTY, 1);
          TR(1, (hh * 16) * 4 + 1);
        }
#pragma unroll 1
        for (int j = 0; j < 15; j += j ? 1 : 2) {
          const int jn = j ? j + 1 : 2;
          wg_wait<0>();
          fence_regs(s);
          TR(1, (hh * 16 + j) * 4 + 2);
          release(n, 1, 2);
          mbar_wait_unless(okp, sb + BAR_BEMPTY + 8 * (j & 1), ((j >> 1) + 1) & 1);
          n = wrap(n + (j == 2 ? 6 : 4));
          exp_store(s, sb + OFF_B + (j & 1) * CH + st_off, 0, 7);
          const uint32_t okk = mbar_test(gbar(n, 0), gpar(n, 0));
          exp_store(s, sb + OFF_B + (j & 1) * CH + st_off, 7, 10);
          TR(1, (hh * 16 + j) * 4 + 3);
          mbar_wait_unless(okk, gbar(n, 0), gpar(n, 0));
          uint32_t a = gaddr(n, 0);
          TR(1, (hh * 16 + jn) * 4);
          qk_steps(s, a, qd, true, 0, 4);
          __syncwarp();
          mbar_arrive_if(lane == 0, sb + BAR_PW + 8 * (j & 1), 1);
          qk_steps(s, a, qd, true, 4, 8);
          wg_commit();
          a = acquire(n, 1);
          qk_steps(s, a, qd + 2 * (CH / 16), false, 0, 8);
          wg_commit();
          publish(sb + BAR_TFULL + 8 * (j & 1));
          wg_wait<1>();
          release(n, 0, 2);
          okp = mbar_test(sb + BAR_BEMPTY + 8 * (jn & 1), ((jn >> 1) + 1) & 1);
          TR(1, (hh * 16 + jn) * 4 + 1);
        }
        wg_wait<0>();
        fence_regs(s);
        TR(1, (hh * 16 + 15) * 4 + 2);
        release(n, 1, 2);
        mbar_wait_unless(okp, sb + BAR_BEMPTY + 8, 0);
        exp_store(s, sb + OFF_B + CH + st_off, 0, 10);
        publish(sb + BAR_TFULL + 8);
        mbar_arrive_if(lane == 0, sb + BAR_PW + 8, 1);
        TR(1, (hh * 16 + 15) * 4 + 3);
        mbar_wait(sb + BAR_LREADY, hh & 1);
        TR(1, 256 + hh);
        uint32_t bad;
        asm volatile("ld.shared.u32 %0, [%1];" : "=r"(bad) : "r"(sb + OFF_FLAG) : "memory");
        if (__shfl_sync(0xffffffffu, bad, 0)) {
          int cta;
          asm volatile("mov.u32 %0, %%ctaid.x;" : "=r"(cta));
          const size_t off = (size_t)(((cta >> 1) & 31) * 4 + hh) * (SK * DH);
          slow_path(sb + OFF_Q, p.kp[cta >> 6] + off, p.vp[cta >> 6] + off, warp, lane);
          publish(sb + BAR_SLOW);
        }
        __syncwarp();
#pragma unroll 1
        for (uint32_t u = 2; u < 6; u++) mbar_wait(sb + BAR_PUB + 8 * u, 1);
        if (hh & 1) {
          const uint32_t rnd = hh >> 1;
#pragma unroll
          for (int i = 0; i < 76; i++) s[i] = 0.f;
          fence_regs(s);
          mbar_wait(sb + BAR_P2GO, rnd);
          n = rnd ? 357 % (2 * NG) : 173 % (2 * NG);
#pragma unroll 1
          for (uint32_t i = 0; i < 8; i++) {
            const uint32_t u = 2 + ((i + 2) & 3);
            TR(1, 264 + rnd * 32 + i * 3);
            if (i >= 4) mbar_wait(sb + BAR_TFULL + 8 * u, rnd);
            TR(1, 265 + rnd * 32 + i * 3);
            if (!(i & 1)) acquire(n, 0);
            TR(1, 266 + rnd * 32 + i * 3);
            const uint32_t a = gaddr(n, 0) + (i & 1) * 512;
            wg_fence();
#pragma unroll
            for (int ks = 0; ks < 4; ks++) wgmma_n152<1>(s, desc<1024>(a + ks * 128), desc<1024>(bd + u * (CH / 16) + ks * 2), 1);
            wg_commit();
            if (rnd && i == TURN_AT) bar_arrive(5, 256);
            wg_wait<1>();
            if (i > 0) releaseB(2 + ((i + 1) & 3), 2);
            if (i & 1) n = wrap(n + 3);
            else if (i > 0 && !(rnd && i == 6)) release(n, -3, 2);
          }
          const uint32_t us = rnd ? F1 : 2;
          mbar_wait(sb + BAR_BEMPTY + 8 * us, 1);
          wg_wait<0>();
          fence_regs(s);
          if (!rnd) { release(n, -3, 2); releaseB(3, 2); }
          store_tile_T<0, 10, false>(s, sb + OFF_B + us * CH + st_off, 1.f);
          publish(sb + BAR_SG + 8 * us);
        }
      }
      TR_DUMP(1);
    } else {
      asm volatile("setmaxnreg.inc.sync.aligned.u32 " REG_O ";");
      const int w = wg - 2;
      float dA[76], dB[76];
#pragma unroll
      for (int i = 0; i < 76; i++) { dA[i] = 0.f; dB[i] = 0.f; }
      fence_regs(dA);
      fence_regs(dB);
      uint32_t n = 0, skip = 1, nslow = 0;
      const uint32_t stw = sb + OFF_B + w * CH + st_off;
      const uint32_t rsa = sb + OFF_B + (w * 4 + warp) * (19 * 128) + lane * 16;
      auto next_chunk0 = [&](int ph) {
        TRO(0);
        mbar_wait(sb + BAR_TFULL, 0);
        TRO(19);
        acquire(n, 0);
        acquire(n, 1);
      };
      next_chunk0(0);
#pragma unroll 1
      for (int ph = 0;; ph++) {
        const bool isP = ph == 2 || ph == 5;
        {
          TRO(1);
          mma_chunk(dA, gaddr(n, 0) + w * 64, bd, 0);
          wg_commit();
          if (ph != 0 && ph != 3) publish(sb + BAR_PUB + 8 * (2 + w));
          wg_wait<1>();
          fence_regs(dB);
          if (ph == 3) {
            release(n, -1, 1);
            releaseB(3, 2);
            mbar_wait(sb + BAR_BEMPTY + 8 * (4 + w), 1);
          }
          if (!skip) store_tile_T<0, 10, false>(dB, stw + 4 * CH, 1.f);
          TRO(2);
          mma_chunk(dB, gaddr(n, 1) + w * 64, bd, 0);
          wg_commit();
          if (ph != 0) publish(sb + (ph == 3 ? BAR_SG : BAR_PUB) + 8 * (4 + w));
          wg_wait<1>();
          release(n, 0, 1);
          n = wrap(n + 2);
        }
        const uint32_t cend = isP ? 6 : 5;
#pragma unroll 1
        for (uint32_t c = 1; c < cend; c++) {
          const uint32_t ut = isP ? 0x103210 : ph == 3 ? 0x20310 : 0x30210, u = (ut >> (4 * c)) & 3, pu = (ut >> (4 * c - 4)) & 3;
          mbar_wait2(sb + (isP && u >= 2 ? BAR_PUB : BAR_TFULL) + 8 * u, u < 2 ? c != 1 : (isP ? 1 : ph & 1), gbar(n, 0), gpar(n, 0));
          uint32_t a = gaddr(n, 0);
          TRO(c < 5 ? 2 + c : 99);
          mma_chunk(dA, a + w * 64, bd + u * (CH / 16), 1);
          wg_commit();
          wg_wait<1>();
          release(n, -1, 1);
          mbar_arrive_if(sig && pu < 2, sb + BAR_BEMPTY + 8 * pu, 3);
          a = acquire(n, 1);
          mma_chunk(dB, a + w * 64, bd + u * (CH / 16), 1);
          wg_commit();
          wg_wait<1>();
          release(n, 0, 1);
          n = wrap(n + 2);
        }
        if (!isP) {
          const int hh = ph - (ph >= 3);
          mbar_wait2(sb + BAR_TFULL + 8, 1, gbar(n, 0), gpar(n, 0));
          TRO(7);
          mma_chunk(dA, gaddr(n, 0) + w * 64, bd + CH / 16, 1);
          wg_commit();
          wg_wait<1>();
          release(n, -1, 1);
          mbar_arrive_if(sig, sb + BAR_X4, 1);
          mbar_wait2(sb + BAR_TFULL + 40, ph & 1, gbar(n, 1), gpar(n, 1));
          if (w == 1) {
            mbar_wait(gbar(n, 2), gpar(n, 2));
            bar_sync(4, 256);
            mma_chunk(dB, gaddr(n, 2) + w * 64, bd + CH / 16, 1);
          }
          mma_chunk(dA, gaddr(n, 1) + w * 64, bd + 5 * (CH / 16), 1);
          wg_commit();
          if (w == 0) bar_arrive(4, 256);
          wg_wait<1>();
          release(n, 0, 1);
          mbar_wait2(gbar(n, 3), gpar(n, 3), gbar(n, 2), gpar(n, 2));
          mbar_wait(sb + BAR_X4, hh & 1);
          wg_wait<0>();
          fence_regs(dA);
          release(n, 1, 1);
          TRO(8);
          store_tile_T<0, Q_SPLIT, true>(dA, stw + 2 * CH, SCALE_LOG2E);
          if (w == 0) {
            mma_chunk(dB, gaddr(n, 2) + w * 64, bd + CH / 16, 1);
            wg_commit();
          }
          mma_chunk(dB, gaddr(n, 3) + w * 64, bd + 5 * (CH / 16), 1);
          wg_commit();
          store_tile_T<Q_SPLIT, 10, true>(dA, stw + 2 * CH, SCALE_LOG2E);
          publish(sb + BAR_PUB + 8 * (2 + w));
          wg_wait<1>();
          release(n, 2, 1);
          TRO(9);
          uint32_t a;
          if (hh > 0) mbar_wait(sb + BAR_ST5, (hh & 1) ^ 1);
          wg_wait<0>();
          fence_regs(dB);
          release(n, 3, 1);
          releaseB(1, 3);
          if (w == 0) mbar_arrive_if(sig, sb + BAR_X6, 1);
          else mbar_wait(sb + BAR_X6, hh & 1);
          store_tile_T<0, 10, true>(dB, stw + 4 * CH, SCALE_LOG2E);
          publish(sb + BAR_PUB + 8 * (4 + w));
          TRO(10);
          if (w == 0) {
            mbar_wait2(sb + BAR_Q0, hh & 1, gbar(n, 6), gpar(n, 6));
            qk_steps(dA, gaddr(n, 6), bd + 2 * (CH / 16), true, 0, 8);
            wg_commit();
            qk_steps(dA, acquire(n, 7), bd + 4 * (CH / 16), false, 0, 8);
            wg_commit();
            mbar_wait(sb + BAR_BEMPTY + 8, 1);
            wg_wait<1>();
            release(n, 6, 2);
            wg_wait<0>();
            fence_regs(dA);
            release(n, 7, 2);
            exp_store(dA, stw + CH, 0, 10);
            publish(sb + BAR_TFULL + 8);
            mbar_arrive_if(lane == 0, sb + BAR_PW + 8, 1);
          }
          n = wrap(n + 10);
          float l[5] = {0.f, 0.f, 0.f, 0.f, 0.f};
          auto row_sums = [&](uint32_t u) {
            const uint32_t ra = rsa + u * CH;
            uint4 v0 = lds128(ra), v1 = lds128(ra + 512), v2 = lds128(ra + 1024);
            l[0] += sum8(v0);
            v0 = lds128(ra + 1536);
            l[1] += sum8(v1);
            v1 = lds128(ra + 2048);
            l[2] += sum8(v2);
            l[3] += sum8(v0);
            l[4] += sum8(v1);
          };
          {
            mbar_wait2(gbar(n, 0), gpar(n, 0), sb + BAR_TFULL, 0);
            TRO(11);
            mma_chunk(dA, gaddr(n, 0) + w * 64, bd, 0);
            wg_commit();
            mma_chunk(dB, acquire(n, 1) + w * 64, bd, 0);
            wg_commit();
            row_sums(0);
            wg_wait<1>();
            release(n, 0, 1);
            mbar_wait2(sb + BAR_TFULL + 8, 0, gbar(n, 2), gpar(n, 2));
            if (w == 1) row_sums(1);
            mma_chunk(dA, gaddr(n, 2) + w * 64, bd + CH / 16, 1);
            wg_commit();
            wg_wait<1>();
            bar_sync(2 + w, 128);
            releaseB(0, 3);
            release(n, 1, 1);
            mma_chunk(dB, acquire(n, 3) + w * 64, bd + CH / 16, 1);
            wg_commit();
            wg_wait<1>();
            release(n, 2, 1);
            if (w == 0) row_sums(1);
            wg_wait<0>();
            release(n, 3, 1);
            bar_sync(2 + w, 128);
            releaseB(1, 3);
            n = wrap(n + 6);
          }
#pragma unroll 1
          for (int j = 2; j < 15; j++) {
            mbar_wait(sb + BAR_PW + 8 * (j & 1), (j >> 1) & 1);
            uint32_t okv;
            {
              const uint32_t ra = rsa + (j & 1) * CH;
              uint4 v0 = lds128(ra), v1 = lds128(ra + 512), v2 = lds128(ra + 1024);
              l[0] += sum8(v0);
              v0 = lds128(ra + 1536);
              l[1] += sum8(v1);
              v1 = lds128(ra + 2048);
              okv = mbar_test(gbar(n, 0), gpar(n, 0));
              l[2] += sum8(v2);
              l[3] += sum8(v0);
              l[4] += sum8(v1);
            }
            mbar_wait_unless(okv, gbar(n, 0), gpar(n, 0));
            okv = mbar_test(gbar(n, 1), gpar(n, 1));
            mbar_wait(sb + BAR_TFULL + 8 * (j & 1), (j >> 1) & 1);
            TRO(j == 14 ? 12 : 99);
            const uint32_t bb = bd + (j & 1) * (CH / 16);
            mma_chunk(dA, gaddr(n, 0) + w * 64, bb, 1);
            wg_commit();
            mbar_wait_unless(okv, gbar(n, 1), gpar(n, 1));
            mma_chunk(dB, gaddr(n, 1) + w * 64, bb, 1);
            wg_commit();
            wg_wait<1>();
            release(n, 0, 1);
            if (j == 14) break;
            wg_wait<0>();
            release(n, 1, 1);
            releaseB(j & 1, 3);
            n = wrap(n + 4);
          }
          mbar_arrive_if(sig, sb + BAR_LTOT, 1);
          n = wrap(n + 2);
          mbar_wait2(gbar(n, 1), gpar(n, 1), gbar(n, 0), gpar(n, 0));
          a = gaddr(n, 0);
          const uint32_t a1 = gaddr(n, 1) + w * 64;
          mbar_wait(sb + BAR_TFULL + 8, 1);
          TRO(13);
          {
            const uint32_t ra = rsa + CH;
            uint4 v0 = lds128(ra), v1 = lds128(ra + 512);
            const uint4 v2 = lds128(ra + 1024);
            mma_chunk(dA, a + w * 64, bd + CH / 16, 1);
            wg_commit();
            l[0] += sum8(v0);
            v0 = lds128(ra + 1536);
            l[1] += sum8(v1);
            v1 = lds128(ra + 2048);
            wg_wait<1>();
            TRO(16);
            releaseB(0, 3);
            release(n, -1, 1);
            l[2] += sum8(v2);
            l[3] += sum8(v0);
            l[4] += sum8(v1);
          }
          {
            const int ln = lane + (n >> 8);
            const bool b0 = ln & 1, b1 = ln & 2, b2 = ln & 4;
            float x0 = __shfl_xor_sync(0xffffffffu, b0 ? l[0] : l[1], 1), x1 = __shfl_xor_sync(0xffffffffu, b0 ? l[2] : l[3], 1);
            float x2 = __shfl_xor_sync(0xffffffffu, l[4], 1);
            wg_fence();
            wgmma_n152<1>(dB, desc<2048>(a1), desc<1024>(bd + CH / 16), 1);
            x0 += b0 ? l[1] : l[0]; x1 += b0 ? l[3] : l[2]; x2 += l[4];
            float y0 = __shfl_xor_sync(0xffffffffu, b1 ? x0 : x1, 2), y1 = __shfl_xor_sync(0xffffffffu, x2, 2);
            wgmma_n152<1>(dB, desc<2048>(a1 + 256), desc<1024>(bd + CH / 16 + 2), 1);
            y0 += b1 ? x1 : x0; y1 += x2;
            float v = __shfl_xor_sync(0xffffffffu, b2 ? y0 : y1, 4);
            wgmma_n152<1>(dB, desc<2048>(a1 + 512), desc<1024>(bd + CH / 16 + 4), 1);
            v += b2 ? y1 : y0;
            const int r = 4 * (ln & 7) + (ln >> 3);
            skip = r < 19 && !(v > 0x1p-60f && v < 0x1p60f);
            asm volatile("{\n.reg .pred p;\nsetp.lt.s32 p, %2, 19;\n@p st.shared.f32 [%0], %1;\n}" ::"r"(sb + OFF_L + ((w * 4 + warp) * 19 + r) * 4), "f"(rcp(v)), "r"(r) : "memory");
            wgmma_n152<1>(dB, desc<2048>(a1 + 768), desc<1024>(bd + CH / 16 + 6), 1);
            wg_commit();
            asm volatile("{\n.reg .pred p, q;\nsetp.ne.b32 p, %0, 0;\nbar.red.or.pred q, 1, 256, p;\nselp.b32 %0, 1, 0, q;\n}" : "+r"(skip)::"memory");
            skip = __any_sync(0xffffffffu, skip);
            asm volatile("{\n.reg .pred p;\nsetp.ne.u32 p, %3, 0;\n@p st.shared.u32 [%0], %1;\n@p mbarrier.arrive.shared::cta.b64 _, [%2];\n}"
                         ::"r"(sb + OFF_FLAG), "r"(skip), "r"(sb + BAR_LREADY), "r"((uint32_t)(sig && w == 0)) : "memory");
          }
          if (skip) { mbar_wait(sb + BAR_SLOW, nslow & 1); nslow++; }
          wg_wait<1>();
          fence_regs(dA);
          release(n, 0, 1);
          TRO(14);
          {
            const uint32_t oa = stw + 2 * CH;
            const uint32_t linv = sb + OFF_L + ((lane + (n >> 8)) & 3) * 8;
            float2 sc[19];
            uint32_t ok0;
#pragma unroll
            for (int g = 0; g < 6; g++) sc[g] = lds64f(linv + g * 32);
#pragma unroll
            for (int g = 0; g < 10; g++) {
              if (g == EPI_SPLIT) {
                wg_wait<0>();
                fence_regs(dB);
                releaseB(1, 3);
                release(n, 1, 1);
                n = wrap(n + 2);
                ok0 = mbar_test(sb + BAR_TFULL, 0) & mbar_test(gbar(n, 0), gpar(n, 0)) & mbar_test(gbar(n, 1), gpar(n, 1));
#pragma unroll
                for (int i = 0; i < 8 * EPI_SPLIT; i++) dB[i] *= (i & 1) ? sc[i >> 2].y : sc[i >> 2].x;
              }
              uint32_t r4[4];
#pragma unroll
              for (int i = 0; i < 4; i++)
                if (8 * g + 2 * i < 76) r4[i] = pack_bf16(dA[8 * g + 2 * i] * sc[2 * g + (i >> 1)].x, dA[8 * g + 2 * i + 1] * sc[2 * g + (i >> 1)].y);
              if (g >= EPI_SPLIT) {
#pragma unroll
                for (int i = 8 * g; i < 8 * g + 8 && i < 76; i++) dB[i] *= (i & 1) ? sc[i >> 2].y : sc[i >> 2].x;
              }
              if (2 * g + 6 < 19) sc[2 * g + 6] = lds64f(linv + (2 * g + 6) * 32);
              if (2 * g + 7 < 19) sc[2 * g + 7] = lds64f(linv + (2 * g + 7) * 32);
              if (g < 9) stsm4t_if(!skip, oa + g * 2048, r4[0], r4[1], r4[2], r4[3]);
              else stsm2t_if(!skip, oa + g * 2048, r4[0], r4[1]);
            }
            fence_regs(dB);
            if (!__all_sync(0xffffffffu, ok0)) next_chunk0(ph + 1);
          }
          TRO(15);
        } else {
          const uint32_t rnd = ph & 1, stage = stw;
          mbar_wait(sb + BAR_PUB + 32, 1);
          uint32_t a = acquire(n, 0);
          TRO(7);
          mma_chunk(dB, a + w * 64, bd + 4 * (CH / 16), 1);
          wg_commit();
          wg_wait<1>();
          release(n, -1, 1);
          releaseB(1, 3);
          mbar_wait(sb + BAR_PUB + 40, 1);
          a = acquire(n, 1);
          mma_chunk(dB, a + w * 64, bd + 5 * (CH / 16), 1);
          wg_commit();
          wg_wait<1>();
          release(n, 0, 1);
          a = acquire(n, 2);
          TRO(8);
          mma_chunk(dA, a + w * 64, bd + 4 * (CH / 16), 1);
          wg_commit();
          mbar_wait(sb + BAR_BEMPTY + 8 * w, 1);
          a = acquire(n, 3);
          wg_wait<1>();
          fence_regs(dB);
          release(n, 1, 1);
          store_tile_T<0, 4, false>(dB, stage, 1.f);
          mma_chunk(dA, a + w * 64, bd + 5 * (CH / 16), 1);
          wg_commit();
          mbar_arrive_if(sig, sb + BAR_P2GO, 1);
          store_tile_T<4, 10, false>(dB, stage, 1.f);
          publish(sb + BAR_SG + 8 * w);
          n = wrap(n + 4);
          a = acquire(n, 0);
          TRO(11);
          mma_chunk(dB, a + w * 64, bd + 4 * (CH / 16), 0);
          wg_commit();
          wg_wait<1>();
          release(n, -2, 1);
          release(n, -1, 1);
          auto pass2 = [&](uint32_t i0, uint32_t i1) {
#pragma unroll 1
            for (uint32_t i = i0; i < i1; i++) {
              const uint32_t u = 2 + ((i + 2) & 3), np = n;
              n = wrap(n + 1 + (i & 1));
              if (i >= 4) mbar_wait(sb + BAR_TFULL + 8 * u, rnd);
              const uint32_t a2 = acquire(n, 0);
              TRO(11 + i);
              mma_chunk(dB, a2 + w * 64, bd + u * (CH / 16), 1);
              wg_commit();
              wg_wait<1>();
              if (!(rnd && i == 4)) release(np, 0, 1);
              releaseB(2 + ((i + 1) & 3), 2);
            }
          };
          const uint32_t i1 = w == (rnd ? F1 : F0) ? ST2_A : ST2_B;
          pass2(1, i1);
          fence_regs(dA);
          mbar_wait(sb + BAR_BEMPTY + 8 * w, 0);
          store_tile_T<0, 10, false>(dA, stage, 1.f);
          publish(sb + BAR_SG + 8 * w);
          pass2(i1, rnd ? 5 : 8);
          if (rnd) break;
          skip = 0;
          n = wrap(n + 1);
          next_chunk0(3);
        }
      }
      bar_sync(w == F1 ? 5 : 6, 256);
#pragma unroll 1
      for (uint32_t i = 5; i < 8; i++) {
        const uint32_t u = 2 + ((i + 2) & 3);
        n = wrap(n + 1 + (i & 1));
        mbar_wait2(sb + BAR_TFULL + 8 * u, 1, gbar(n, 0), gpar(n, 0));
        const uint32_t a2 = gaddr(n, 0);
        TRO5(11 + i);
        mma_chunk(dB, a2 + w * 64, bd + u * (CH / 16), 1);
        wg_commit();
      }
      if (w == F1) { bar_arrive(6, 256); mbar_wait(sb + BAR_BEMPTY + 8 * F1, 1); }
      wg_wait<2>();
      releaseB(5 - F1, 2);
      const uint32_t us = w == F1 ? 1 - F1 : 5 - F1;
      mbar_wait(sb + BAR_BEMPTY + 8 * us, 1);
      wg_wait<0>();
      fence_regs(dB);
      store_tile_T<0, 10, false>(dB, stw + (us - w) * CH, 1.f);
      publish(sb + BAR_SG + 8 * us);
      TRO5(20);
      TRO_DUMP(wg);
    }
  }
}

typedef CUresult (*EncodeFn)(CUtensorMap*, CUtensorMapDataType, cuuint32_t, void*, const cuuint64_t*, const cuuint64_t*, const cuuint32_t*,
                             const cuuint32_t*, CUtensorMapInterleave, CUtensorMapSwizzle, CUtensorMapL2promotion, CUtensorMapFloatOOBfill);

void make_map4(EncodeFn fn, CUtensorMap* m, const void* ptr, uint64_t rows, uint64_t cols, uint32_t box_chunks = 2) {
  cuuint64_t dims[4] = {64, 8, cols / 64, rows / 8};
  cuuint64_t strides[3] = {cols * 2, 128, cols * 16};
  cuuint32_t box[4] = {64, 8, box_chunks, 16 / box_chunks}, es[4] = {1, 1, 1, 1};
  fn(m, CU_TENSOR_MAP_DATA_TYPE_BFLOAT16, 4, const_cast<void*>(ptr), dims, strides, box, es, CU_TENSOR_MAP_INTERLEAVE_NONE,
     CU_TENSOR_MAP_SWIZZLE_128B, CU_TENSOR_MAP_L2_PROMOTION_L2_128B, CU_TENSOR_MAP_FLOAT_OOB_FILL_NONE);
}
void make_map2(EncodeFn fn, CUtensorMap* m, const void* ptr, uint64_t rows, uint64_t cols, uint32_t box_rows) {
  cuuint64_t dims[2] = {cols, rows};
  cuuint64_t strides[1] = {cols * 2};
  cuuint32_t box[2] = {64, box_rows}, es[2] = {1, 1};
  fn(m, CU_TENSOR_MAP_DATA_TYPE_BFLOAT16, 2, const_cast<void*>(ptr), dims, strides, box, es, CU_TENSOR_MAP_INTERLEAVE_NONE,
     CU_TENSOR_MAP_SWIZZLE_128B, CU_TENSOR_MAP_L2_PROMOTION_L2_128B, CU_TENSOR_MAP_FLOAT_OOB_FILL_NONE);
}

}

extern "C" void kernel_launch(void* const* d_in, const int* in_sizes, int n_in, void* d_out, int out_size) {
  static EncodeFn fn = nullptr;
  if (!fn) {
    void* f = nullptr;
    cudaDriverEntryPointQueryResult st;
    cudaGetDriverEntryPoint("cuTensorMapEncodeTiled", &f, cudaEnableDefault, &st);
    fn = reinterpret_cast<EncodeFn>(f);
    cudaFuncSetAttribute(fused_mha_kernel, cudaFuncAttributeMaxDynamicSharedMemorySize, SMEM_BYTES);
  }
  Params p;
  for (int i = 0; i < 2; i++) {
    make_map2(fn, &p.x[i], d_in[5 * i + 0], NB * SQ, DM, NQ);
    make_map4(fn, &p.k[i], d_in[5 * i + 1], NB * NH * SK, DH);
    make_map4(fn, &p.v[i], d_in[5 * i + 2], NB * NH * SK, DH);
    make_map4(fn, &p.wq[i], d_in[5 * i + 3], DM, NH * DH);
    make_map4(fn, &p.wo[i], d_in[5 * i + 4], NH * DH, DM);
    make_map4(fn, &p.wo6[i], d_in[5 * i + 4], NH * DH, DM, 1);
    p.kp[i] = (const __nv_bfloat16*)d_in[5 * i + 1];
    p.vp[i] = (const __nv_bfloat16*)d_in[5 * i + 2];
  }
  make_map2(fn, &p.out[0], d_out, NB * SQ, 2 * DM, 40);
  make_map2(fn, &p.out[1], d_out, NB * SQ, 2 * DM, 32);
  p.outp = (__nv_bfloat16*)d_out;
  fused_mha_kernel<<<128, 512, SMEM_BYTES>>>(p);
}
```
